```python
import torch

def _softmax(x, axis=-1):
    return torch.softmax(x, dim=axis)
def _gelu(x):
    return torch.nn.functional.gelu(x, approximate="tanh")
def _silu(x):
    return torch.nn.functional.silu(x)
def _sigmoid(x):
    return torch.sigmoid(x)
def _layernorm(x, axis=-1, eps=1e-5):
    m = x.mean(dim=axis, keepdim=True)
    v = x.var(dim=axis, keepdim=True, unbiased=False)
    return (x - m) / torch.sqrt(v + eps)
def _scatter_add(tgt, idx, src, axis=0):
    return tgt.clone().index_add_(axis, idx, src)
def _segment_sum(src, seg, n):
    out = torch.zeros((n,) + src.shape[1:], dtype=src.dtype)
    return out.index_add_(0, seg, src)
def _pad(x, pw):
    flat = tuple(v for pair in reversed(pw) for v in pair)
    return torch.nn.functional.pad(x, flat)

kernel_name = 'recurrent_scan__linear_kernel_hedgehog__dense_activation_silu__prompt'

def setup_inputs():

    _w = (lambda a: (lambda t: t.to(torch.bfloat16) if t.is_floating_point() else t)(torch.as_tensor(a)))
    def _A_setup():
        B, S, D, H = 1, 2048, 640, 32
        Dh = D // H
        return {
            "x": _w((lambda *s: torch.randn(*s, dtype=torch.bfloat16) * 0.05)(B, S, D)),
            "wqkv": _w((lambda *s: torch.randn(*s, dtype=torch.bfloat16) * 0.4)(D, 3 * D)),
            "w_phi": _w((lambda *s: torch.randn(*s, dtype=torch.bfloat16) * 0.4)(H, Dh, Dh) * (Dh ** -0.5)),
            "wo": _w((lambda *s: torch.randn(*s, dtype=torch.bfloat16) * 0.2)(D, D)),
        }
    _A_in = _A_setup()

    def _B_setup():
        B, S, D, F = 1, 2048, 640, 1728
        return {
            "x": _w((lambda *s: torch.randn(*s, dtype=torch.bfloat16) * 0.05)(B, S, D)),
            "w1": _w((lambda *s: torch.randn(*s, dtype=torch.bfloat16) * 0.4)(D, F) * (D ** -0.5)),
            "w2": _w((lambda *s: torch.randn(*s, dtype=torch.bfloat16) * 0.1)(F, D) * (F ** -0.5)),
        }
    _B_in = _B_setup()

    return {
        "A_x": _A_in["x"],
        "A_wqkv": _A_in["wqkv"],
        "A_w_phi": _A_in["w_phi"],
        "A_wo": _A_in["wo"],
        "B_x": _B_in["x"],
        "B_w1": _B_in["w1"],
        "B_w2": _B_in["w2"],
    }

def reference(A_x, A_wqkv, A_w_phi, A_wo, B_x, B_w1, B_w2):
    def _A_ref(x, wqkv, w_phi, wo):
        B, S, D = x.shape
        H = 32; Dh = D // H
        qkv = (lambda x, *d: x.permute(*d))((x @ wqkv).reshape(B, S, 3, H, Dh), 2, 0, 3, 1, 4)
        q, k, v = qkv[0], qkv[1], qkv[2]
        pq = torch.einsum("bhsd,hdf->bhsf", q, w_phi)
        pk = torch.einsum("bhsd,hdf->bhsf", k, w_phi)
        phi_q = torch.concatenate([_softmax(pq, axis=-1), _softmax(-pq, axis=-1)], axis=-1)
        phi_k = torch.concatenate([_softmax(pk, axis=-1), _softmax(-pk, axis=-1)], axis=-1)
        kv = torch.einsum("bhsf,bhsd->bhfd", phi_k, v)
        z  = torch.einsum("bhsf->bhf", phi_k)
        num = torch.einsum("bhqf,bhfd->bhqd", phi_q, kv)
        den = torch.einsum("bhqf,bhf->bhq", phi_q, z)[..., None] + 1e-6
        o = num / den
        return (lambda x, *d: x.permute(*d))(o, 0, 2, 1, 3).reshape(B, S, D) @ wo

    def _B_ref(x, w1, w2):
        h = torch.einsum("bsd,df->bsf", x, w1)
        h = _silu(h)
        out = torch.einsum("bsf,fd->bsd", h, w2)
        return out

    x = A_x
    xn = _layernorm(x, axis=-1)
    s = _A_ref(xn, A_wqkv, A_w_phi, A_wo)
    g = _silu(_B_ref(xn, B_w1, B_w2))
    return x + s * g
```

```cpp
#include <cuda_runtime.h>
#include <cuda_bf16.h>
#include <cuda.h>
#include <stdint.h>
#include <type_traits>
#include <stddef.h>

typedef __nv_bfloat16 bf16;

template<int TA,int TB,uint32_t IA,uint32_t IB> __device__ __forceinline__ void wgmma_n24(float (&d)[12], uint64_t a, uint64_t b, int sd) {
  asm volatile("{\n.reg .pred p;\n.reg .b64 da, db;\nsetp.ne.b32 p, %14, 0;\n"
    "add.s64 da, %12, %17;\nadd.s64 db, %13, %18;\n"
    "wgmma.mma_async.sync.aligned.m64n24k16.f32.bf16.bf16 {%0,%1,%2,%3,%4,%5,%6,%7,%8,%9,%10,%11}, da, db, p, 1, 1, %15, %16;\n}\n"
    : "+f"(d[0]),"+f"(d[1]),"+f"(d[2]),"+f"(d[3]),"+f"(d[4]),"+f"(d[5]),"+f"(d[6]),"+f"(d[7]),"+f"(d[8]),"+f"(d[9]),"+f"(d[10]),"+f"(d[11])
    : "l"(a), "l"(b), "r"(sd), "n"(TA), "n"(TB), "n"(IA), "n"(IB));
}

template<int TA,int TB,uint32_t IA,uint32_t IB> __device__ __forceinline__ void wgmma_n104(float (&d)[52], uint64_t a, uint64_t b, int sd) {
  asm volatile("{\n.reg .pred p;\n.reg .b64 da, db;\nsetp.ne.b32 p, %54, 0;\n"
    "add.s64 da, %52, %57;\nadd.s64 db, %53, %58;\n"
    "wgmma.mma_async.sync.aligned.m64n104k16.f32.bf16.bf16 {%0,%1,%2,%3,%4,%5,%6,%7,%8,%9,%10,%11,%12,%13,%14,%15,%16,%17,%18,%19,%20,%21,%22,%23,%24,%25,%26,%27,%28,%29,%30,%31,%32,%33,%34,%35,%36,%37,%38,%39,%40,%41,%42,%43,%44,%45,%46,%47,%48,%49,%50,%51}, da, db, p, 1, 1, %55, %56;\n}\n"
    : "+f"(d[0]),"+f"(d[1]),"+f"(d[2]),"+f"(d[3]),"+f"(d[4]),"+f"(d[5]),"+f"(d[6]),"+f"(d[7]),"+f"(d[8]),"+f"(d[9]),"+f"(d[10]),"+f"(d[11]),"+f"(d[12]),"+f"(d[13]),"+f"(d[14]),"+f"(d[15]),"+f"(d[16]),"+f"(d[17]),"+f"(d[18]),"+f"(d[19]),"+f"(d[20]),"+f"(d[21]),"+f"(d[22]),"+f"(d[23]),"+f"(d[24]),"+f"(d[25]),"+f"(d[26]),"+f"(d[27]),"+f"(d[28]),"+f"(d[29]),"+f"(d[30]),"+f"(d[31]),"+f"(d[32]),"+f"(d[33]),"+f"(d[34]),"+f"(d[35]),"+f"(d[36]),"+f"(d[37]),"+f"(d[38]),"+f"(d[39]),"+f"(d[40]),"+f"(d[41]),"+f"(d[42]),"+f"(d[43]),"+f"(d[44]),"+f"(d[45]),"+f"(d[46]),"+f"(d[47]),"+f"(d[48]),"+f"(d[49]),"+f"(d[50]),"+f"(d[51])
    : "l"(a), "l"(b), "r"(sd), "n"(TA), "n"(TB), "n"(IA), "n"(IB));
}

template<int TA,int TB,uint32_t IA,uint32_t IB> __device__ __forceinline__ void wgmma_n160(float (&d)[80], uint64_t a, uint64_t b, int sd) {
  asm volatile("{\n.reg .pred p;\n.reg .b64 da, db;\nsetp.ne.b32 p, %82, 0;\n"
    "add.s64 da, %80, %85;\nadd.s64 db, %81, %86;\n"
    "wgmma.mma_async.sync.aligned.m64n160k16.f32.bf16.bf16 {%0,%1,%2,%3,%4,%5,%6,%7,%8,%9,%10,%11,%12,%13,%14,%15,%16,%17,%18,%19,%20,%21,%22,%23,%24,%25,%26,%27,%28,%29,%30,%31,%32,%33,%34,%35,%36,%37,%38,%39,%40,%41,%42,%43,%44,%45,%46,%47,%48,%49,%50,%51,%52,%53,%54,%55,%56,%57,%58,%59,%60,%61,%62,%63,%64,%65,%66,%67,%68,%69,%70,%71,%72,%73,%74,%75,%76,%77,%78,%79}, da, db, p, 1, 1, %83, %84;\n}\n"
    : "+f"(d[0]),"+f"(d[1]),"+f"(d[2]),"+f"(d[3]),"+f"(d[4]),"+f"(d[5]),"+f"(d[6]),"+f"(d[7]),"+f"(d[8]),"+f"(d[9]),"+f"(d[10]),"+f"(d[11]),"+f"(d[12]),"+f"(d[13]),"+f"(d[14]),"+f"(d[15]),"+f"(d[16]),"+f"(d[17]),"+f"(d[18]),"+f"(d[19]),"+f"(d[20]),"+f"(d[21]),"+f"(d[22]),"+f"(d[23]),"+f"(d[24]),"+f"(d[25]),"+f"(d[26]),"+f"(d[27]),"+f"(d[28]),"+f"(d[29]),"+f"(d[30]),"+f"(d[31]),"+f"(d[32]),"+f"(d[33]),"+f"(d[34]),"+f"(d[35]),"+f"(d[36]),"+f"(d[37]),"+f"(d[38]),"+f"(d[39]),"+f"(d[40]),"+f"(d[41]),"+f"(d[42]),"+f"(d[43]),"+f"(d[44]),"+f"(d[45]),"+f"(d[46]),"+f"(d[47]),"+f"(d[48]),"+f"(d[49]),"+f"(d[50]),"+f"(d[51]),"+f"(d[52]),"+f"(d[53]),"+f"(d[54]),"+f"(d[55]),"+f"(d[56]),"+f"(d[57]),"+f"(d[58]),"+f"(d[59]),"+f"(d[60]),"+f"(d[61]),"+f"(d[62]),"+f"(d[63]),"+f"(d[64]),"+f"(d[65]),"+f"(d[66]),"+f"(d[67]),"+f"(d[68]),"+f"(d[69]),"+f"(d[70]),"+f"(d[71]),"+f"(d[72]),"+f"(d[73]),"+f"(d[74]),"+f"(d[75]),"+f"(d[76]),"+f"(d[77]),"+f"(d[78]),"+f"(d[79])
    : "l"(a), "l"(b), "r"(sd), "n"(TA), "n"(TB), "n"(IA), "n"(IB));
}

template<int TA,int TB,uint32_t IA,uint32_t IB> __device__ __forceinline__ void wgmma_n192(float (&d)[96], uint64_t a, uint64_t b, int sd) {
  asm volatile("{\n.reg .pred p;\n.reg .b64 da, db;\nsetp.ne.b32 p, %98, 0;\n"
    "add.s64 da, %96, %101;\nadd.s64 db, %97, %102;\n"
    "wgmma.mma_async.sync.aligned.m64n192k16.f32.bf16.bf16 {%0,%1,%2,%3,%4,%5,%6,%7,%8,%9,%10,%11,%12,%13,%14,%15,%16,%17,%18,%19,%20,%21,%22,%23,%24,%25,%26,%27,%28,%29,%30,%31,%32,%33,%34,%35,%36,%37,%38,%39,%40,%41,%42,%43,%44,%45,%46,%47,%48,%49,%50,%51,%52,%53,%54,%55,%56,%57,%58,%59,%60,%61,%62,%63,%64,%65,%66,%67,%68,%69,%70,%71,%72,%73,%74,%75,%76,%77,%78,%79,%80,%81,%82,%83,%84,%85,%86,%87,%88,%89,%90,%91,%92,%93,%94,%95}, da, db, p, 1, 1, %99, %100;\n}\n"
    : "+f"(d[0]),"+f"(d[1]),"+f"(d[2]),"+f"(d[3]),"+f"(d[4]),"+f"(d[5]),"+f"(d[6]),"+f"(d[7]),"+f"(d[8]),"+f"(d[9]),"+f"(d[10]),"+f"(d[11]),"+f"(d[12]),"+f"(d[13]),"+f"(d[14]),"+f"(d[15]),"+f"(d[16]),"+f"(d[17]),"+f"(d[18]),"+f"(d[19]),"+f"(d[20]),"+f"(d[21]),"+f"(d[22]),"+f"(d[23]),"+f"(d[24]),"+f"(d[25]),"+f"(d[26]),"+f"(d[27]),"+f"(d[28]),"+f"(d[29]),"+f"(d[30]),"+f"(d[31]),"+f"(d[32]),"+f"(d[33]),"+f"(d[34]),"+f"(d[35]),"+f"(d[36]),"+f"(d[37]),"+f"(d[38]),"+f"(d[39]),"+f"(d[40]),"+f"(d[41]),"+f"(d[42]),"+f"(d[43]),"+f"(d[44]),"+f"(d[45]),"+f"(d[46]),"+f"(d[47]),"+f"(d[48]),"+f"(d[49]),"+f"(d[50]),"+f"(d[51]),"+f"(d[52]),"+f"(d[53]),"+f"(d[54]),"+f"(d[55]),"+f"(d[56]),"+f"(d[57]),"+f"(d[58]),"+f"(d[59]),"+f"(d[60]),"+f"(d[61]),"+f"(d[62]),"+f"(d[63]),"+f"(d[64]),"+f"(d[65]),"+f"(d[66]),"+f"(d[67]),"+f"(d[68]),"+f"(d[69]),"+f"(d[70]),"+f"(d[71]),"+f"(d[72]),"+f"(d[73]),"+f"(d[74]),"+f"(d[75]),"+f"(d[76]),"+f"(d[77]),"+f"(d[78]),"+f"(d[79]),"+f"(d[80]),"+f"(d[81]),"+f"(d[82]),"+f"(d[83]),"+f"(d[84]),"+f"(d[85]),"+f"(d[86]),"+f"(d[87]),"+f"(d[88]),"+f"(d[89]),"+f"(d[90]),"+f"(d[91]),"+f"(d[92]),"+f"(d[93]),"+f"(d[94]),"+f"(d[95])
    : "l"(a), "l"(b), "r"(sd), "n"(TA), "n"(TB), "n"(IA), "n"(IB));
}

template<int N,int TA,int TB,uint32_t IA,uint32_t IB> __device__ __forceinline__ void wgmma(float (&d)[N/2], uint64_t a, uint64_t b, int sd) {
  if constexpr (N==24) wgmma_n24<TA,TB,IA,IB>(d,a,b,sd);
  if constexpr (N==104) wgmma_n104<TA,TB,IA,IB>(d,a,b,sd);
  if constexpr (N==160) wgmma_n160<TA,TB,IA,IB>(d,a,b,sd);
  if constexpr (N==192) wgmma_n192<TA,TB,IA,IB>(d,a,b,sd);
}

#define T_O 34
#define T_SYNC 35
#define NTHR 384
namespace {

constexpr int S_ = 2048, D_ = 640;
constexpr int CS_N = 456;
constexpr int KV_FLOATS = 32 * 960;
static_assert(KV_FLOATS + 8 * CS_N <= 128 * 80 * 4, "z");
constexpr int WP_KG = 33 * 128;

constexpr int SLOT = 40960, NSLOT = 4;
constexpr int PH_OFF = NSLOT * SLOT;
constexpr int PH_HS = 10272;
constexpr int VH_OFF = PH_OFF + 4 * PH_HS;
constexpr int VH_HS = 6176;
constexpr int CS_OFF = VH_OFF + 4 * VH_HS;
constexpr int CS_QS = 464;
constexpr int BAR_OFF = CS_OFF + 4 * CS_QS;
constexpr int SMEM_BYTES = BAR_OFF + 176;
static_assert(SMEM_BYTES <= 232448, "smem");
constexpr uint32_t SB0 = 0x400;
constexpr int B_FULL = 0, B_EMPTY = 32, B_CS = 64, B_KVB = 72, B_XRDY = 80, B_XG = 88, B_XS = 96, B_SLAB = 104, B_SLAB2 = 112, B_DEP = 120, B_EPOCH = 168;
constexpr int SL_W1 = PH_OFF, SL_QKV = SL_W1 + 15360, SL_WT = SL_QKV + 19200, SL_PHI = SL_WT + 1920, SL_ST = SL_PHI + 3200;

constexpr int NB_PUB = 1, NB_ALL = 7, NB_WG0 = 8, NB_HLP = 10;

constexpr int FL_SYNC = 120, FL_EPOCH = 128, FL_N = 136;

struct Params {
  CUtensorMap mX, mW1, mW1s, mWts, mQs, mWp2, mWp3, mW2a, mW2n, mWoa;
  const bf16 *x, *wqkv, *wphi, *w1, *w2, *wo;
  bf16* out;
  uint64_t dsw[14], dns[14];
  int tile[64];
  int one;
};

struct Scratch {
  unsigned flags[FL_N * 32];
  float2 stats[S_];
  float z[2][128 * 80 * 4];
  uint8_t wp[8 * 80 * WP_KG];
  uint8_t wx[2 * 37 * 8192];
  uint8_t ho[16 * 37 * 16384];
};

}

__device__ __align__(1024) Scratch g_s;
#define TR(role, idx)
#define TRC(idx)

namespace {

__device__ __forceinline__ uint32_t smem_u32(const void* p) { return (uint32_t)__cvta_generic_to_shared(p); }
__device__ __forceinline__ void mbar_init(uint32_t b, int c) { asm volatile("mbarrier.init.shared::cta.b64 [%0], %1;" ::"r"(b), "r"(c) : "memory"); }
__device__ __forceinline__ void mbar_expect(uint32_t b, int bytes) { asm volatile("mbarrier.arrive.expect_tx.shared::cta.b64 _, [%0], %1;" ::"r"(b), "r"(bytes) : "memory"); }
__device__ __forceinline__ void mbar_arrive(uint32_t b) { asm volatile("mbarrier.arrive.shared::cta.b64 _, [%0];" ::"r"(b) : "memory"); }
__device__ __forceinline__ void mbar_arrive_remote(uint32_t rb) { asm volatile("mbarrier.arrive.relaxed.cluster.shared::cluster.b64 _, [%0];" ::"r"(rb) : "memory"); }
__device__ __forceinline__ void mbar_wait_long(uint32_t b, uint32_t ph) {
  asm volatile("{\n.reg .pred p, c;\n.reg .u32 n;\nmov.u32 n, 0;\nWL:\n"
               "mbarrier.try_wait.parity.shared::cta.b64 p, [%0], %1;\n"
               "add.u32 n, n, 1;\nsetp.lt.and.u32 c, n, 100000, !p;\n@c bra WL;\n}" ::"r"(b), "r"(ph) : "memory");
}
__device__ __forceinline__ void mbar_wait(uint32_t b, uint32_t ph, uint32_t& n) {
  asm volatile("{\n.reg .pred p;\nWL:\nmbarrier.try_wait.parity.shared::cta.b64 p, [%1], %2;\nadd.u32 %0, %0, 1;\n@!p bra WL;\n}" : "+r"(n) : "r"(b), "r"(ph) : "memory");
}
__device__ __forceinline__ unsigned ld_rlx(const unsigned* p) { unsigned v; asm volatile("ld.relaxed.gpu.global.u32 %0, [%1];" : "=r"(v) : "l"(p) : "memory"); return v; }
__device__ __forceinline__ void flag_wait(const unsigned* f, unsigned target) {
  asm volatile("{\n.reg .pred p;\n.reg .u32 n;\n.reg .s32 v;\nmov.u32 n, 0;\nFL:\n"
               "ld.relaxed.gpu.global.s32 v, [%0];\nsub.s32 v, v, %1;\nadd.u32 n, n, 1;\n"
               "setp.lt.s32 p, v, 0;\nsetp.lt.and.u32 p, n, 40000, p;\n@p bra FL;\n}" ::"l"(f), "r"(target) : "memory");
}
__device__ __forceinline__ bool elect_one() {
  uint32_t e;
  asm volatile("{\n.reg .pred p;\nelect.sync _|p, 0xffffffff;\nselp.u32 %0, 1, 0, p;\n}" : "=r"(e));
  return e != 0;
}
__device__ __forceinline__ void fence_async_glob() { asm volatile("fence.proxy.async.global;" ::: "memory"); }
__device__ __forceinline__ void fence_async_smem() { asm volatile("fence.proxy.async.shared::cta;" ::: "memory"); }
template <int ID, int N> __device__ __forceinline__ void nb_sync() { asm volatile("bar.sync %0, %1;" ::"n"(ID), "n"(N) : "memory"); }
template <int ID, int N> __device__ __forceinline__ void nb_arrive() { asm volatile("bar.arrive %0, %1;" ::"n"(ID), "n"(N) : "memory"); }

__device__ __forceinline__ void tma1d(uint32_t dst, const void* src, int bytes, uint32_t bar) {
  asm volatile("cp.async.bulk.shared::cluster.global.mbarrier::complete_tx::bytes [%0], [%1], %2, [%3];" ::"r"(dst), "l"(src), "r"(bytes), "r"(bar) : "memory");
}
__device__ __forceinline__ void tma2d(uint32_t dst, const CUtensorMap* m, int c0, int c1, uint32_t bar) {
  asm volatile("cp.async.bulk.tensor.2d.shared::cluster.global.mbarrier::complete_tx::bytes [%0], [%1, {%3,%4}], [%2];" ::"r"(dst), "l"(m), "r"(bar), "r"(c0), "r"(c1) : "memory");
}
__device__ __forceinline__ void tma3d(uint32_t dst, const CUtensorMap* m, int c1, int c2, uint32_t bar) {
  asm volatile("cp.async.bulk.tensor.3d.shared::cluster.global.mbarrier::complete_tx::bytes [%0], [%1, {%5,%3,%4}], [%2];" ::"r"(dst), "l"(m), "r"(bar), "r"(c1), "r"(c2), "r"(0) : "memory");
}
__device__ __forceinline__ void tma3d0(uint32_t dst, const CUtensorMap* m, int c0, int c1, uint32_t bar) {
  asm volatile("cp.async.bulk.tensor.3d.shared::cluster.global.mbarrier::complete_tx::bytes [%0], [%1, {%3,%4,%5}], [%2];" ::"r"(dst), "l"(m), "r"(bar), "r"(c0), "r"(c1), "r"(0) : "memory");
}
__device__ __forceinline__ void tma5d(uint32_t dst, const CUtensorMap* m, int c2, int c4, uint32_t bar) {
  asm volatile("cp.async.bulk.tensor.5d.shared::cluster.global.mbarrier::complete_tx::bytes [%0], [%1, {%5,%5,%3,%5,%4}], [%2];" ::"r"(dst), "l"(m), "r"(bar), "r"(c2), "r"(c4), "r"(0) : "memory");
}
__device__ __forceinline__ void prefetch_map(const CUtensorMap* m) { asm volatile("prefetch.tensormap [%0];" ::"l"(m) : "memory"); }
__device__ __forceinline__ void prefetch_l2(const void* p) { asm volatile("prefetch.global.L2 [%0];" ::"l"(p) : "memory"); }

__host__ __device__ constexpr uint32_t dlo(uint32_t addr, uint32_t lbo) { return (addr >> 4) + ((lbo >> 4) << 16); }
__host__ __device__ constexpr uint64_t dhi(uint32_t sbo, uint32_t sw) { return (uint64_t)((sbo >> 4) | (sw << 30)) << 32; }
__device__ __forceinline__ void wg_fence() { asm volatile("wgmma.fence.sync.aligned;" ::: "memory"); }
__device__ __forceinline__ void wg_commit() { asm volatile("wgmma.commit_group.sync.aligned;" ::: "memory"); }
template <int N> __device__ __forceinline__ void wg_wait() { asm volatile("wgmma.wait_group.sync.aligned %0;" ::"n"(N) : "memory"); }
template <int I> using IC = std::integral_constant<int, I>;
template <class T> __device__ __forceinline__ void keep(T*& p) { asm volatile("" : "+l"(p)); }
__device__ __forceinline__ void keep(float& a, float& b) { asm volatile("" : "+f"(a), "+f"(b)); }
template <int N> __device__ __forceinline__ void pin(float (&d)[N]) {
#pragma unroll
  for (int i = 0; i < N; i++) asm volatile("" : "+f"(d[i])::"memory");
}

__device__ __forceinline__ uint32_t pack2(float lo, float hi) { uint32_t r; asm("cvt.rn.bf16x2.f32 %0, %1, %2;" : "=r"(r) : "f"(hi), "f"(lo)); return r; }
__device__ __forceinline__ float ex2f(float x) { float y; asm("ex2.approx.ftz.f32 %0, %1;" : "=f"(y) : "f"(x)); return y; }
__device__ __forceinline__ float rcpf(float x) { float y; asm("rcp.approx.ftz.f32 %0, %1;" : "=f"(y) : "f"(x)); return y; }
__device__ __forceinline__ float tanhf_(float x) { float y; asm("tanh.approx.f32 %0, %1;" : "=f"(y) : "f"(x)); return y; }
__device__ __forceinline__ float silu_half(float y) { return fmaf(y, tanhf_(y), y); }

__device__ __forceinline__ uint4 ldg128(const void* p) { uint4 v; asm volatile("ld.global.nc.v4.u32 {%0,%1,%2,%3}, [%4];" : "=r"(v.x), "=r"(v.y), "=r"(v.z), "=r"(v.w) : "l"(p)); return v; }
__device__ __forceinline__ float4 ldcg128f(const void* p) { float4 v; asm volatile("ld.global.cg.v4.f32 {%0,%1,%2,%3}, [%4];" : "=f"(v.x), "=f"(v.y), "=f"(v.z), "=f"(v.w) : "l"(p) : "memory"); return v; }
__device__ __forceinline__ void stg128(void* p, uint32_t a, uint32_t b, uint32_t c, uint32_t d) { asm volatile("st.global.v4.u32 [%0], {%1,%2,%3,%4};" ::"l"(p), "r"(a), "r"(b), "r"(c), "r"(d) : "memory"); }
__device__ __forceinline__ void stg64(void* p, uint32_t a, uint32_t b) { asm volatile("st.global.v2.u32 [%0], {%1,%2};" ::"l"(p), "r"(a), "r"(b) : "memory"); }
__device__ __forceinline__ void stg32(void* p, uint32_t a) { asm volatile("st.global.u32 [%0], %1;" ::"l"(p), "r"(a) : "memory"); }
__device__ __forceinline__ void sts128(uint32_t p, uint32_t a, uint32_t b, uint32_t c, uint32_t d) { asm volatile("st.shared.v4.u32 [%0], {%1,%2,%3,%4};" ::"r"(p), "r"(a), "r"(b), "r"(c), "r"(d) : "memory"); }
__device__ __forceinline__ void sts32(uint32_t p, uint32_t a) { asm volatile("st.shared.u32 [%0], %1;" ::"r"(p), "r"(a) : "memory"); }
__device__ __forceinline__ void sts64(uint32_t p, uint32_t a, uint32_t b) { asm volatile("st.shared.v2.u32 [%0], {%1,%2};" ::"r"(p), "r"(a), "r"(b) : "memory"); }
__device__ __forceinline__ void sts64f(uint32_t p, float a, float b) { asm volatile("st.shared.v2.f32 [%0], {%1,%2};" ::"r"(p), "f"(a), "f"(b) : "memory"); }
__device__ __forceinline__ float4 lds128f(uint32_t p) { float4 v; asm volatile("ld.shared.v4.f32 {%0,%1,%2,%3}, [%4];" : "=f"(v.x), "=f"(v.y), "=f"(v.z), "=f"(v.w) : "r"(p) : "memory"); return v; }
__device__ __forceinline__ uint4 lds128(uint32_t p) { uint4 v; asm volatile("ld.shared.v4.u32 {%0,%1,%2,%3}, [%4];" : "=r"(v.x), "=r"(v.y), "=r"(v.z), "=r"(v.w) : "r"(p) : "memory"); return v; }
__device__ __forceinline__ void red1(float* p, float a) { asm volatile("red.relaxed.gpu.global.add.f32 [%0], %1;" ::"l"(p), "f"(a) : "memory"); }
__device__ __forceinline__ void red2(float* p, float a, float b) { asm volatile("red.relaxed.gpu.global.add.v2.f32 [%0], {%1,%2};" ::"l"(p), "f"(a), "f"(b) : "memory"); }
template <int OFF>
__device__ __forceinline__ void st_async4(uint32_t ra, uint32_t a, uint32_t b, uint32_t c, uint32_t d, uint32_t rbar) {
  asm volatile("st.async.weak.shared::cluster.mbarrier::complete_tx::bytes.v4.b32 [%0+%6], {%1,%2,%3,%4}, [%5];" ::"r"(ra), "r"(a), "r"(b), "r"(c), "r"(d), "r"(rbar), "n"(OFF) : "memory");
}
__device__ __forceinline__ float bf_lo(uint32_t v) { return __uint_as_float(v << 16); }
__device__ __forceinline__ float bf_hi(uint32_t v) { return __uint_as_float(v & 0xffff0000u); }
__device__ __forceinline__ uint32_t lds32(uint32_t p) { uint32_t v; asm volatile("ld.shared.u32 %0, [%1];" : "=r"(v) : "r"(p) : "memory"); return v; }
__device__ __forceinline__ uint2 lds64(uint32_t p) { uint2 v; asm volatile("ld.shared.v2.u32 {%0,%1}, [%2];" : "=r"(v.x), "=r"(v.y) : "r"(p) : "memory"); return v; }
__device__ __forceinline__ uint4 ldsm4t(uint32_t p) { uint4 v; asm volatile("ldmatrix.sync.aligned.m8n8.x4.trans.shared.b16 {%0,%1,%2,%3}, [%4];" : "=r"(v.x), "=r"(v.y), "=r"(v.z), "=r"(v.w) : "r"(p) : "memory"); return v; }
__device__ __forceinline__ uint32_t movtrans(uint32_t a) { uint32_t d; asm volatile("movmatrix.sync.aligned.m8n8.trans.b16 %0, %1;" : "=r"(d) : "r"(a)); return d; }
__device__ __forceinline__ void mma16816(float (&d)[4], uint32_t a0, uint32_t a1, uint32_t a2, uint32_t a3, uint32_t b0, uint32_t b1) {
  asm volatile("mma.sync.aligned.m16n8k16.row.col.f32.bf16.bf16.f32 {%0,%1,%2,%3}, {%4,%5,%6,%7}, {%8,%9}, {%10,%10,%10,%10};"
               : "=f"(d[0]), "=f"(d[1]), "=f"(d[2]), "=f"(d[3]) : "r"(a0), "r"(a1), "r"(a2), "r"(a3), "r"(b0), "r"(b1), "f"(0.f));
}
__device__ __forceinline__ void mma16816a(float (&d)[4], uint32_t a0, uint32_t a1, uint32_t a2, uint32_t a3, uint32_t b0, uint32_t b1) {
  asm volatile("mma.sync.aligned.m16n8k16.row.col.f32.bf16.bf16.f32 {%0,%1,%2,%3}, {%4,%5,%6,%7}, {%8,%9}, {%0,%1,%2,%3};"
               : "+f"(d[0]), "+f"(d[1]), "+f"(d[2]), "+f"(d[3]) : "r"(a0), "r"(a1), "r"(a2), "r"(a3), "r"(b0), "r"(b1));
}
__device__ __forceinline__ void mma1688(float (&d)[4], uint32_t a0, uint32_t a1, uint32_t b0) {
  asm volatile("mma.sync.aligned.m16n8k8.row.col.f32.bf16.bf16.f32 {%0,%1,%2,%3}, {%4,%5}, {%6}, {%0,%1,%2,%3};"
               : "+f"(d[0]), "+f"(d[1]), "+f"(d[2]), "+f"(d[3]) : "r"(a0), "r"(a1), "r"(b0));
}
__device__ __forceinline__ uint32_t hadd2bf(uint32_t a, uint32_t b) { uint32_t d; asm("add.rn.bf16x2 %0, %1, %2;" : "=r"(d) : "r"(a), "r"(b)); return d; }
__device__ __forceinline__ uint32_t hfma2bf(uint32_t a, uint32_t b, uint32_t c) { uint32_t d; asm("fma.rn.bf16x2 %0, %1, %2, %3;" : "=r"(d) : "r"(a), "r"(b), "r"(c)); return d; }
__device__ __forceinline__ uint32_t hmul2bf(uint32_t a, uint32_t b) { uint32_t d; asm("mul.rn.bf16x2 %0, %1, %2;" : "=r"(d) : "r"(a), "r"(b)); return d; }

template <int N, int MODE, int TC, int KK>
__device__ __forceinline__ void mma_k16(float (&acc)[N / 2], uint64_t da, uint64_t db, int sd) {
  constexpr uint32_t slot = SB0 + (TC < 0 ? 0 : (TC & 3) * SLOT);
  constexpr uint32_t aslot = (TC >= 10 && TC < 20) ? SB0 + ((19 - TC) & 3) * SLOT : slot;
  wgmma<N, 0, MODE != 1, MODE == 2 ? dlo(slot + KK * 4096, 2048) : dlo(aslot + KK * 32, 16),
        MODE == 1 ? dlo(slot + 16384 + KK * N * 32, N * 16) : dlo(slot + 16384 + KK * 2048, 8192)>(acc, da, db, sd);
}
template <int N, int MODE, int TC, bool RETIRE = true>
__device__ __forceinline__ void mma_step(float (&acc)[N / 2], uint32_t sb, int t, uint64_t da, uint64_t db, bool leader, uint32_t& nw, bool first = false, int half = -1) {
  if (TC < 0) { da += (uint32_t)((t & 3) * (SLOT / 16)); db += (uint32_t)((t & 3) * (SLOT / 16)); }
  if (half >= 0) { da += (uint32_t)(half * 512); db += (uint32_t)(half * 256); }
  mbar_wait(sb + BAR_OFF + B_FULL + (t & 3) * 8, (t >> 2) & 1, nw);
  wg_fence();
  mma_k16<N, MODE, TC, 0>(acc, da, db, first ? 0 : 1);
  mma_k16<N, MODE, TC, 1>(acc, da, db, 1);
  if (half < 0) { mma_k16<N, MODE, TC, 2>(acc, da, db, 1); mma_k16<N, MODE, TC, 3>(acc, da, db, 1); }
  wg_commit();
  if (RETIRE) {
    wg_wait<1>();
    if (leader && t > 0) mbar_arrive(sb + BAR_OFF + B_EMPTY + ((t - 1) & 3) * 8);
  }
}

template <int N> __device__ __forceinline__ void lds_cs(float (&c)[N], uint32_t a) {
#pragma unroll
  for (int i = 0; i < N / 4; i++) { const float4 v = lds128f(a + i * 16); c[4 * i] = v.x; c[4 * i + 1] = v.y; c[4 * i + 2] = v.z; c[4 * i + 3] = v.w; }
}
template <int NA>
__device__ __forceinline__ void fm_logits(const float (&acc)[NA], const float (&c)[20], float nm0, float nm1, float (&a)[20], float (&b)[20]) {
#pragma unroll
  for (int j = 0; j < 10; j++) {
    a[2 * j] = fmaf(c[2 * j], nm0, acc[4 * j]); a[2 * j + 1] = fmaf(c[2 * j + 1], nm0, acc[4 * j + 1]);
    b[2 * j] = fmaf(c[2 * j], nm1, acc[4 * j + 2]); b[2 * j + 1] = fmaf(c[2 * j + 1], nm1, acc[4 * j + 3]);
  }
}
__device__ __forceinline__ void fm_range(const float (&a)[20], float& mx, float& mn) {
  float m0 = fmaxf(a[0], a[1]), m1 = fmaxf(a[2], a[3]), n0 = fminf(a[0], a[1]), n1 = fminf(a[2], a[3]);
#pragma unroll
  for (int i = 4; i < 20; i += 2) { m0 = fmaxf(m0, a[i]); m1 = fmaxf(m1, a[i + 1]); n0 = fminf(n0, a[i]); n1 = fminf(n1, a[i + 1]); }
  mx = fmaxf(m0, m1); mn = fminf(n0, n1);
}
__device__ __forceinline__ void fm_args(const float (&a)[20], float sc, float (&ep)[20], float (&en)[20]) {
  float mx, mn;
  fm_range(a, mx, mn);
  const float op = -sc * mx, on = sc * mn;
#pragma unroll
  for (int i = 0; i < 20; i++) { ep[i] = fmaf(a[i], sc, op); en[i] = fmaf(a[i], -sc, on); }
}
__device__ __forceinline__ float fm_exp(float (&e)[20]) {
#pragma unroll
  for (int i = 0; i < 20; i++) e[i] = ex2f(e[i]);
  float s0 = e[0] + e[1], s1 = e[2] + e[3];
#pragma unroll
  for (int i = 4; i < 20; i += 2) { s0 += e[i]; s1 += e[i + 1]; }
  return rcpf(s0 + s1);
}
__device__ __forceinline__ void fm_put(const float (&ep)[20], float ip, const float (&en)[20], float in, uint32_t ps) {
  uint32_t p[10], n[10];
#pragma unroll
  for (int j = 0; j < 10; j++) { p[j] = pack2(ep[2 * j] * ip, ep[2 * j + 1] * ip); n[j] = pack2(en[2 * j] * in, en[2 * j + 1] * in); }
  sts128(ps, p[0], p[1], p[2], p[3]); sts128(ps + 2048, p[4], p[5], p[6], p[7]); sts128(ps + 4096, p[8], p[9], n[8], n[9]);
  sts128(ps + 6144, n[0], n[1], n[2], n[3]); sts128(ps + 8192, n[4], n[5], n[6], n[7]);
}

}

__global__ void __cluster_dims__(2, 1, 1) __launch_bounds__(NTHR, 1) fused_kernel(const __grid_constant__ Params p) {
  extern __shared__ __align__(1024) uint8_t smem_raw[];
  const uint32_t sb = smem_u32(smem_raw);
  const int tid = threadIdx.x;
  if ((sb & 0x3FFFF) != SB0) return;
  const int pos = p.tile[blockIdx.x >> 1] + (blockIdx.x & 1);
  const int r = pos >> 3, c = pos & 7, ks = c & 1;
#define BMAP 0
  const int rb = BMAP == 0 ? r : BMAP == 1 ? (r & ~1) + ((c >> 1) & 1) : (r & ~3) + (c >> 1);
  const int jb = BMAP == 0 ? c >> 1 : BMAP == 1 ? 2 * (r & 1) + (c >> 2) : r & 3;
  const int a0 = 5 * (jb >> 1) + 3 * (jb & 1);
  const int pg = 10 * (jb >> 1) + 4 + (jb & 1);
  const uint  const int warp = __shfl_sync(~0u, tid >> 5, 0), lane = tid & 31;
  if (warp == 8) {
    if (elect_one()) {
      prefetch_map(&p.mX); prefetch_map(&p.mW1);
#pragma unroll
      for (int s = 0; s < NSLOT; s++) mbar_init(bars + B_FULL + s * 8, 1);
      asm volatile("fence.mbarrier_init.release.cluster;" ::: "memory");
#pragma unroll 1
      for (int t = 0; t < NSLOT; t++) {
        mbar_expect(bars + B_FULL + t * 8, 40960);
        tma2d(sb + t * SLOT, &p.mX, t * 64, r * 128, bars + B_FULL + t * 8);
        tma3d(sb + t * SLOT + 16384, &p.mW1, t * 64, 3 * c, bars + B_FULL + t * 8);
        TR(2, t);
      }
    }
  } else if (warp == 9) {
    if (elect_one()) {
      prefetch_map(&p.mQs); prefetch_map(&p.mWts); prefetch_map(&p.mW1s);
#pragma unroll
      for (int s = 0; s < 17; s++) mbar_init(bars + B_EMPTY + s * 8, (s < 4 || s == 10) ? 2 : (s == 5 ? 4 : (s == 6 ? 8 : 1)));
      asm volatile("fence.mbarrier_init.release.cluster;" ::: "memory");
    }
  } else if (warp == 10) {
    if (lane < 28) prefetch_l2(lane < 16 ? (const char*)p.x + (uint32_t)((pos * 16 + lane) * 1280) : (const char*)p.w1 + (uint32_t)((pos >> 1) * 3456 + ((pos & 1) * 12 + lane - 16) * 128));
  }
if (s != 9) mbar_init(bars + B_EMPTY + s * 8, (s < 4 || s == 10) ? 2 : (s == 5 ? 4 : (s == 6 ? 8 : 1)));
      asm volatile("fence.mbarrier_init.release.cluster;" ::: "memory");
    }
  } else if (warp == 10) {
#define ACQ(bytes) const uint32_t slot = sb + (t & 3) * SLOT, fb = bars + B_FULL + (t & 3) * 8; \
                   mbar_wait_long(fb + B_EMPTY, ((t >> 2) & 1) ^ 1); mbar_expect(fb, bytes); TR(2, t);
        mbar_expect(bars + B_SLAB, 19200 + 1920 + 3200);
        tma1d(sb + SL_PHI, p.wphi + c * 1600, 3200, bars + B_SLAB);
        tma3d0(sb + SL_QKV, &p.mQs, c * 80, r * 40, bars + B_SLAB);
        tma2d(sb + SL_WT, &p.mWts, 1536 + c * 24, r * 40, bars + B_SLAB);
        mbar_expect(bars + B_XG, 20480); mbar_expect(bars + B_XS, 20480);
 sb + (t & 3) * SLOT, fb = bars + B_FULL + (t & 3) * 8; \
                   mbar_wait_long(fb + B_EMPTY, ((t >> 2) & 1) ^ 1); mbar_expect(fb, bytes); TR(2, t);
        mbar_expect(bars + B_SLAB2, 15360);
        tma3d(sb + SL_W1, &p.mW1s, r * 40, 3 * c, bars + B_SLAB2);
        mbar_expect(bars + B_XG, 20480); mbar_expect(bars + B_XS, 20480);
#pragma unroll 1
        for (; t < 30; t++) {
          const int k = t < 10 ? t : (t < 20 ? 19 - t : t - 20);
          const bool ldx = (0x3F0FC3FFu >> t) & 1;
          ACQ((ldx ? 16384 : 0) + (t < 10 ? 24576 : (t < 20 ? 20480 : 13312)))
          if (ldx) tma2d(sb + (k & 3) * SLOT, &p.mX, k * 64, r * 128, fb);
          if (t == 10 || t == 20) { mbar_wait_long(bars + B_DEP + (t == 20 ? 8 : 0), 0); fence_async_glob(); if (t == 10) TR(2, 49); }
          tma3d(slot + 16384, t < 10 ? &p.mW1 : (t < 20 ? &p.mWp2 : &p.mWp3), t < 10 ? k * 64 : (t < 20 ? 0 : 20), t < 10 ? 3 * c : c * 80 + k * 8, fb);
          if (t == 4) { mbar_expect(bars + B_SLAB2, 15360); tma3d(sb + SL_W1, &p.mW1s, r * 40, 3 * c, bars + B_SLAB2); }
          if (t >= 5 && t < 10) prefetch_map(&p.mWp2 + (t - 5));
          if (t >= 10 && t < 20) {
            asm volatile("cp.async.bulk.prefetch.L2.global [%0], 1728;" ::"l"((const char*)p.w2 + (uint32_t)((pos * 10 + k) * 1728)) : "memory");
            asm volatile("cp.async.bulk.prefetch.L2.global [%0], 640;" ::"l"((const char*)p.wo + (uint32_t)((pos * 10 + k) * 640)) : "memory");
          }
        }
#pragma unroll 1
        for (; t < 49; t++) {
          const int ch = t < 42 ? 12 * ks + t - 30 : (t == 42 ? 24 + 2 * ks : (t == 43 ? 25 : 5 * ks + t - 17));
          const CUtensorMap* m = t < 42 ? &p.mW2a : (t < 44 ? &p.mW2n : &p.mWoa);
          const int kc = (t < 44 ? ch : ch - 27) * 8;
          ACQ(40960)
          if (t == T_SYNC) {
#pragma unroll
            for (int j = 0; j < 4; j++) asm volatile("red.relaxed.gpu.global.add.u32 [%0], 1;" ::"l"(g_s.flags + (FL_SYNC + j) * 32) : "memory");
          }
          tma5d(slot + 16384, m, kc, a0 + ks, fb);
          tma5d(slot + 24576, m, kc, a0 + 1 - ks, fb);
          if (jb & 1) tma1d(slot + 32768, g_s.wx + ((jb >> 1) * 37 + ch) * 8192, 8192, fb);
          else tma5d(slot + 32768, m, kc, a0 + 2, fb);
          if (t == 30 || t == 42 || t == 44) {
            mbar_wait_long(bars + B_DEP + (t == 30 ? 16 : (t == 42 ? 32 : 40)), 0); fence_async_glob();
            TR(2, t == 30 ? 50 : (t == 42 ? 51 : 52));
          }
          tma1d(slot, g_s.ho + (rb * 37 + ch) * 16384, 16384, fb);
          if (t == T_SYNC) { flag_wait(g_s.flags + (FL_SYNC + (pos & 3)) * 32, lds32(bars + B_EPOCH) * 128 + 128); mbar_arrive(bars + B_KVB); }
        }
#undef ACQ
      }

    } else {
      const uint32_t ht = tid - 288;
      if (ht == 0) { sts32(bars + B_EPOCH, ld_rlx(g_s.flags + FL_EPOCH * 32)); mbar_arrive(bars + B_SLAB2); }
      nb_sync<NB_HLP, 96>();
      const unsigned epoch = lds32(bars + B_EPOCH);
      if (ht < 80) reinterpret_cast<float4*>(g_s.z[(epoch + 1) & 1])[(uint32_t)(pos * 80 + ht)] = make_float4(0.f, 0.f, 0.f, 0.f);
      float* z = g_s.z[epoch & 1];
      if (warp == 11) {
        const uint32_t pp = pos >> 1, co = (lane >> 2) * 81920 + (pos & 1) * 640 + 320 + (lane & 3) * 16;
        const char* sp = (const char*)p.w2 + (co + ((pp & 14) * 4 + (pp >> 4) * 2 + (pp & 1)) * 1280);
        const char* so = (const char*)p.wo + (co + pp * 1280);
        const char* sm = lane < 12 ? (const char*)p.w2 + (co + pp * 1280 + 24 * 81920) : so - 3 * 81920;
        uint8_t* d = g_s.wx + (((pos & 1) * 37 + (lane >> 2)) * 8192 + pp * 128 + (((lane & 3) ^ (pp & 7)) << 4));
        mbar_wait_long(bars + B_SLAB2, 0);
        if (lane == 0) TR(3, 19);
        uint4 v[5];
        v[0] = ldg128(sp); v[1] = ldg128(sp + 8 * 81920); v[2] = ldg128(sp + 16 * 81920); v[3] = ldg128(sm);
        if (lane < 20) v[4] = ldg128(so + 5 * 81920);
#pragma unroll
        for (int k = 0; k < 5; k++) if (k < 4 || lane < 20) stg128(d + k * 65536, v[k].x, v[k].y, v[k].z, v[k].w);
      }
#pragma unroll 1
      for (int i = 0; i < 6; i++) {
        const bool colev = ((0xB >> i) & 1) && lane == 0;
        unsigned* const fl = g_s.flags + (uint32_t)(((lane ? 6 : i) * 16 + (colev ? c : ((warp == 10 && lane == 0) ? rb : r))) * 32);
        const bool act = lane < (i == 1 ? 2 : 1);
        if (warp == 9 + 2 * (i & 1)) {
          asm volatile("bar.sync %0, 288;" ::"r"(NB_PUB + i) : "memory");
          if (lane == 0) TR(3, 2 * i);
          if (act) {
            asm volatile("fence.proxy.async;" ::: "memory");
            asm volatile("red.relaxed.gpu.global.add.u32 [%0], %1;" ::"l"(fl), "r"(colev ? 1 : 2) : "memory");
          }
          if (lane == 0) TR(3, 2 * i + 1);
        }
        if (warp == 10) {
          if (act) flag_wait(fl, epoch * 16 + 16);
          __syncwarp();
          if (lane == 0) mbar_arrive(bars + B_DEP + i * 8);
          if (i == 1) {
            if (lane == 0) TR(3, 18);
            float4 v[6];
            const float* src = z + (KV_FLOATS + c * CS_N + lane * 4);
#pragma unroll
            for (int k = 0; k < 4; k++) v[k] = ldcg128f(src + k * 128);
            v[4] = ldcg128f(&g_s.stats[r * 128 + lane * 2]); v[5] = ldcg128f(&g_s.stats[r * 128 + 64 + lane * 2]);
            const uint32_t d = sb + CS_OFF + (lane & 1) * 2 * CS_QS + (lane >> 1) * 8;
#pragma unroll
            for (int k = 0; k < 4; k++)
              if (k < 3 || lane < CS_N / 4 - 96) { sts64f(d + k * 128, v[k].x, v[k].y); sts64f(d + k * 128 + CS_QS, v[k].z, v[k].w); }
#pragma unroll
            for (int k = 0; k < 2; k++)
              sts128(sb + SL_ST + k * 512 + lane * 16, __float_as_uint(v[4 + k].x), __float_as_uint(v[4 + k].y), __float_as_uint(v[4 + k].z), __float_as_uint(v[4 + k].w));
            __syncwarp();
            if (lane == 0) { mbar_arrive(bars + B_CS); TR(3, 12); }
          }
        }
        if (i == 3) {
          const uint32_t sl = ht >> 3, h = (sl * 11) >> 5;
          int s4 = 2 * (sl - 3 * h) + (ht & 1) - (h & 1);
          if (s4 < 0) s4 = 5;
          const float* src = z + (c * 3840 + sl * 320 + (ht & 7) * 4);
          const uint32_t dst = sb + VH_OFF + h * 2304 + (s4 >> 1) * 768 + (s4 & 1) * 8 + ((ht & 7) >> 1) * 16;
          mbar_wait_long(bars + B_DEP + 24, 0);
          if (ht == 32) TR(3, 13);
          float4 v[10];
#pragma unroll
          for (int j = 0; j < 10; j++) v[j] = ldcg128f(src + j * 32);
          sts64(dst + 640, 0, 0); sts64(dst + 704, 0, 0);
#pragma unroll
          for (int j = 0; j < 10; j++) sts64(dst + j * 64, pack2(v[j].x, v[j].y), pack2(v[j].z, v[j].w));
          fence_async_smem();
          __syncwarp();
          if (lane == 0) mbar_arrive(bars + B_KVB);
          if (ht == 32) TR(3, 14);
        }
      }
    }
  } else {
    asm volatile("setmaxnreg.inc.sync.aligned.u32 224;");
    const int wg = warp >> 2, W = warp, g = lane >> 2, q = lane & 3;
    const bool leader
    const bool on = p.one != 0;
    float acc1[96];
    {
      const uint32_t ones = 0x3f803f80u, l7 = lane & 7, fh = W & 3;
      const uint32_t srow = pos * 16 + W * 2 + (lane >> 4);
      uint32_t wl = sb + SL_PHI + fh * 800 + 4 * q + (4 * (g >> 1) + (g & 1)) * 40, wh = sb + SL_PHI + fh * 800 + 4 * q + (g & 3) * 40 + 640;
      uint32_t ws = sb + SL_QKV + (wg ? 0 : 6400) + g * 160 + fh * 40 + 8 * q, w8 = sb + SL_QKV + (wg ? 0 : 6400) + g * 160 + fh * 40 + 4 * (q & 1) + 32;
      uint32_t n = wg * 160 + 8 * (g >> 1) + 2 * fh + (g & 1);
      const char* xp = (const char*)p.x + (srow * (2u * D_) + (lane & 15) * 16u);
      auto vrow = [&](int col) { const int h = (col * 205) >> 12, f = col - h * 20; return 80 + 8 * (f >> 1) + 2 * h + (f & 1); };
      uint32_t r0 = vrow(W * 8 + g), r1 = W < 2 ? vrow(64 + W * 8 + g) : 224 + W * 8 + g;
      uint32_t va = sb + SL_QKV + 12800 + W * 16, vb = W < 2 ? va + 128 : sb + SL_WT + min(W - 2, 2) * 16;
      const uint32_t pb = W < 2 ? 160 : 48;
      uint32_t vc = (lane & 8) ? vb + (32 + l7) * pb : va + (32 + l7) * 160;
      va += lane * 160; vb += lane * pb;
      asm volatile("" : "+r"(wl), "+r"(wh), "+r"(ws), "+r"(w8), "+r"(n), "+l"(xp), "+r"(r0), "+r"(r1), "+r"(va), "+r"(vb), "+r"(vc));
#pragma unroll 1
      for (int t = 0; t < 4; t++) { STEPR(192, 0, acc1, t, t == 0) }
      uint4 xs[5];
#pragma unroll
      for (int i = 0; i < 5; i++) xs[i] = ldg128(xp + 256 * i);
      mbar_wait(bars + B_SLAB, 0, nw);
      if (tid == 0) TR(3, 20);
      uint8_t* const wpc = g_s.wp + (uint32_t)((c * 80 + r * 5) * WP_KG + q * 4);
      auto put5 = [&](uint32_t row, uint32_t a, uint32_t b, uint32_t cc, uint32_t d, uint32_t e) {
        uint8_t* dst = wpc + row * 16;
        stg32(dst, a); stg32(dst + WP_KG, b); stg32(dst + 2 * WP_KG, cc); stg32(dst + 3 * WP_KG, d); stg32(dst + 4 * WP_KG, e);
      };
      const uint4 t0 = ldsm4t(va), t1 = ldsm4t(vb), t2 = ldsm4t(vc);
      uint32_t k0[16];
      {
        uint32_t fa[9];
        fa[0] = lds32(wl); fa[1] = lds32(wl + 16); fa[2] = lds32(wl + 80); fa[3] = lds32(wl + 96);
        fa[4] = lds32(wh); fa[5] = lds32(wh + 16); fa[6] = lds32(wl + 32); fa[7] = lds32(wl + 112); fa[8] = lds32(wh + 32);
        uint2 fb[5]; uint32_t fb8[5];
#pragma unroll
        for (int nt = 0; nt < 5; nt++) { fb[nt] = lds64(ws + nt * 1280); fb8[nt] = lds32(w8 + nt * 1280); }
#pragma unroll
        for (int i = 0; i < 9; i++) fa[i] = movtrans(fa[i]);
        if (q >= 2) { fa[4] = 0; fa[5] = 0; fa[8] = 0; }
        put5(r0, t0.x, t0.y, t0.z, t0.w, t2.x);
        if (W < 5) put5(r1, t1.x, t1.y, t1.z, t1.w, t2.y);
#pragma unroll
        for (int nt = 0; nt < 5; nt++) {
          float e0[4], e1[4];
          mma16816(e0, fa[0], fa[1], fa[2], fa[3], fb[nt].x, fb[nt].y);
          mma1688(e0, fa[4], fa[5], fb8[nt]);
          mma16816(e1, fa[6], fa[6], fa[7], fa[7], fb[nt].x, fb[nt].y);
          mma1688(e1, fa[8], fa[8], fb8[nt]);
          k0[2 * nt] = pack2(e0[0], e0[1]); k0[2 * nt + 1] = pack2(e0[2], e0[3]); k0[nt < 4 ? 12 + nt : 10] = pack2(e1[0], e1[1]);
        }
      }
      STEP(192, 0, acc1, 4)
      auto putk = [&]() {
        put5(n, k0[0], k0[2], k0[4], k0[6], k0[8]); put5(n + 32, k0[1], k0[3], k0[5], k0[7], k0[9]);
        if (g < 4) put5(n + 64, k0[12], k0[13], k0[14], k0[15], k0[10]);
      };
      if (wg == 0) putk();
      nb_arrive<NB_PUB, 288>();
      STEP(192, 0, acc1, 5)
      if (wg != 0) putk();
      mbar_wait(bars + B_SLAB2, 0, nw);
      auto swz = [&](uint32_t C) { return (C >> 3) * 5120 + (((C & 7) ^ l7) << 4); };
      const uint32_t wa = sb + SL_W1;
      const uint4 c0 = ldsm4t(wa + lane * 128 + swz(3 * W)), c1 = ldsm4t(wa + lane * 128 + swz(3 * W + 1)), c2 = ldsm4t(wa + lane * 128 + swz(3 * W + 2));
      const uint4 c3 = ldsm4t(wa + (32 + l7) * 128 + swz(3 * W + min(lane >> 3, 2)));
      const uint32_t x0 = __shfl_sync(~0u, xs[0].x, 0, 16) << 16;
      const uint32_t pv = ((x0 >> 16) | x0) ^ 0x80008000u;
      float s[4] = {0.f, 0.f, 0.f, 0.f}, u[4] = {0.f, 0.f, 0.f, 0.f}, w[4] = {0.f, 0.f, 0.f, 0.f};
      float u0[4], u1[4], u2[4], e1[4] = {0.f, 0.f, 0.f, 0.f}, e2[4] = {0.f, 0.f, 0.f, 0.f}, e3[4] = {0.f, 0.f, 0.f, 0.f}, p0[4], p1[4], p2[4], p3[4];
      uint4 ys[5];
#pragma unroll
      for (int i = 0; i < 5; i++) { ys[i].x = hadd2bf(xs[i].x, pv); ys[i].y = hadd2bf(xs[i].y, pv); ys[i].z = hadd2bf(xs[i].z, pv); ys[i].w = hadd2bf(xs[i].w, pv); }
      if (on) {
#pragma unroll
        for (int i = 0; i < 5; i++) {
          mma16816a(s, xs[i].x, xs[i].y, xs[i].z, xs[i].w, ones, ones);
          mma16816a(u, ys[i].x, ys[i].z, ys[i].y, ys[i].w, ys[i].x, ys[i].y);
          mma16816a(w, ys[i].x, ys[i].z, ys[i].y, ys[i].w, ys[i].z, ys[i].w);
        }
        mma16816(u0, c0.x, c0.y, c0.z, c0.w, ones, ones); mma16816(u1, c1.x, c1.y, c1.z, c1.w, ones, ones); mma16816(u2, c2.x, c2.y, c2.z, c2.w, ones, ones);
        mma1688(e1, c3.x, c3.y, ones); mma1688(e2, c3.z, k0[10], ones);
        mma16816(p0, k0[0], k0[1], k0[2], k0[3], ones, ones); mma16816(p1, k0[12], k0[13], k0[14], k0[15], ones, ones);
        mma16816a(p0, k0[4], k0[5], k0[6], k0[7], ones, ones); mma1688(p0, k0[8], k0[9], ones);
        mma16816(p2, t0.x, t0.y, t0.z, t0.w, ones, ones); mma16816(p3, t1.x, t1.y, t1.z, t1.w, ones, ones); mma1688(e3, t2.x, t2.y, ones);
      }
      STEP(192, 0, acc1, 6)
      if (on) {
        float* zcs = g_s.z[lds32(bars + B_EPOCH) & 1] + (KV_FLOATS + c * CS_N);
        if (q != 2 || g < 4) red1(zcs + (192 + (q < 3 ? n + 32 * q : r0)), q == 0 ? p0[0] : q == 1 ? p0[2] : q == 2 ? p1[0] + p1[2] + e2[2] : p2[0] + p2[2] + e3[0]);
        if (q < 3 || W < 5)
          red1(zcs + (uint32_t)(q < 3 ? W * 24 + 8 * q + g : 192 + r1), q == 0 ? u0[0] + u0[2] + e1[0] : q == 1 ? u1[0] + u1[2] + e1[2] : q == 2 ? u2[0] + u2[2] + e2[0] : p3[0] + p3[2] + e3[2]);
        float m = s[0] + s[2], v = (g & 1) ? u[1] + w[3] : u[0] + w[2];
        if (q != (g >> 1)) v = 0.f;
        m += __shfl_xor_sync(~0u, m, 4); m += __shfl_xor_sync(~0u, m, 8);
#pragma unroll
        for (int o = 8; o > 0; o >>= 1) v += __shfl_xor_sync(~0u, v, o);
        const float nmean = m * (-1.f / D_);
        m = __uint_as_float(x0) + nmean;
        float rstd;
        asm("rsqrt.approx.ftz.f32 %0, %1;" : "=f"(rstd) : "f"(fmaxf(fmaf(v, 1.f / D_, -m * m), 0.f) + 1e-5f));
        if ((lane & 15) == 0) stg64(&g_s.stats[srow], __float_as_uint(rstd), __float_as_uint(nmean));
      }
      nb_arrive<NB_PUB + 1, 288>();
#pragma unroll 1
      for (int t = 7; t < 10; t++) { STEPR(192, 0, acc1, t) }
    }

FLOATS + c * CS_N);
          if (q != 2 || g < 4) red1(zcs + (192 + (q < 3 ? n + 32 * q : r0)), v0);
          if (q < 3 || W < 5) red1(zcs + (uint32_t)(q < 3 ? W * 24 + 8 * q + g : 192 + r1), q == 0 ? u0[0] + u0[2] + e1[0] : q == 1 ? u1[0] + u1[2] + e1[2] : q == 2 ? u2[0] + u2[2] + e2[0] : v1);
          float m = s[0] + s[2], v = (g & 1) ? u[1] + w[3] : u[0] + w[2];
          if (q != (g >> 1)) v = 0.f;
          m += __shfl_xor_sync(~0u, m, 4); m += __shfl_xor_sync(~0u, m, 8);
#pragma unroll
          for (int o = 8; o > 0; o >>= 1) v += __shfl_xor_sync(~0u, v, o);
          const float nmean = m * (-1.f / D_);
          m = __uint_as_float(x0) + nmean;
          float rstd;
          asm("rsqrt.approx.ftz.f32 %0, %1;" : "=f"(rstd) : "f"(fmaxf(fmaf(v, 1.f / D_, -m * m), 0.f) + 1e-5f));
          if ((lane & 15) == 0) stg64(&g_s.stats[srow], __float_as_uint(rstd), __float_as_uint(nmean));
        }
        nb_arrive<NB_PUB + 1, 288>();
        RETIRE(5)
      }
#pragma unroll 1
      for (int t = 6; t < 10; t++) { STEPR(192, 0, acc1, t) }
    }

    float acc2[80];
    STEP(160, 1, acc2, 10, true)
    pin(acc1);
    mbar_wait(bars + B_CS, 0, nw);
    float2 st0, st1;
    { const uint2 a = lds64(sb + SL_ST + (W * 16 + g) * 8), b = lds64(sb + SL_ST + (W * 16 + g) * 8 + 64);
      st0 = make_float2(__uint_as_float(a.x), __uint_as_float(a.y)); st1 = make_float2(__uint_as_float(b.x), __uint_as_float(b.y)); }
    const uint32_t csq = sb + CS_OFF + q * CS_QS;
    uint8_t* const hth = g_s.ho + (uint32_t)(r * 37 * 16384 + W * 256 + g * 16);
    {
      float cc[2][8];
      lds_cs(cc[0], csq); lds_cs(cc[1], csq + 32);
      uint8_t* d = hth + (uint32_t)((c * 24 + 2 * q) * 2048);
      keep(d);
      float h0, h1;
      auto unit = [&](auto IC, auto RC) {
        constexpr int i = decltype(IC)::value, R = decltype(RC)::value;
        const float hs = R ? h1 : h0, nm = R ? st1.y : st0.y;
        uint32_t u[4];
#pragma unroll
        for (int jj = 0; jj < 4; jj++)
          u[jj] = pack2(silu_half(hs * fmaf(cc[i & 1][2 * jj], nm, acc1[16 * i + 4 * jj + 2 * R])), silu_half(hs * fmaf(cc[i & 1][2 * jj + 1], nm, acc1[16 * i + 4 * jj + 2 * R + 1])));
        if (R && i < 4) lds_cs(cc[i & 1], csq + (i + 2) * 32);
        stg128(d + ((i >> 1) * 8 + (i & 1)) * 2048 + R * 128, u[0], u[1], u[2], u[3]);
      };
      auto triple = [&](auto KC) {
        constexpr int k = decltype(KC)::value;
        STEP(160, 1, acc2, 11 + 3 * k)
        if (k == 0) { h0 = 0.5f * st0.x; h1 = 0.5f * st1.x; keep(h0, h1); }
        if (on) unit(IC<2 * k>(), IC<0>());
        STEP(160, 1, acc2, 12 + 3 * k)
        if (on) { unit(IC<2 * k>(), IC<1>()); unit(IC<2 * k + 1>(), IC<0>()); }
        STEP(160, 1, acc2, 13 + 3 * k)
        if (on) unit(IC<2 * k + 1>(), IC<1>());
      };
      triple(IC<0>()); triple(IC<1>()); triple(IC<2>());
      nb_arrive<NB_PUB + 2, 288>();
    }

    constexpr float LOG2E = 1.4426950408889634f;
    const uint32_t phs = sb + PH_OFF + q * PH_HS + W * 256 + g * 16;
    float acc3[52], accg[80];
    {
      float a[20], b[20];
      {
        float cc[20], cv[20];
        lds_cs(cc, csq + 24 * 8);
        lds_cs(cv, csq + 34 * 8);
        STEP(104, 1, acc3, 20, true)
        pin(acc2);
        fm_logits(acc2, cc, st0.y, st1.y, a, b);
        const uint32_t vhs = sb + VH_OFF + q * VH_HS + W * 256 + g * 16;
        uint32_t u[10], w[10];
#pragma unroll
        for (int j = 0; j < 10; j++) {
          u[j] = pack2(st0.x * fmaf(cv[2 * j], st0.y, acc2[40 + 4 * j]), st0.x * fmaf(cv[2 * j + 1], st0.y, acc2[41 + 4 * j]));
          w[j] = pack2(st1.x * fmaf(cv[2 * j], st1.y, acc2[42 + 4 * j]), st1.x * fmaf(cv[2 * j + 1], st1.y, acc2[43 + 4 * j]));
        }
        sts128(vhs, u[0], u[1], u[2], u[3]); sts128(vhs + 2048, u[4], u[5], u[6], u[7]); sts128(vhs + 4096, u[8], u[9], 0x00003f80u, 0u);
        sts128(vhs + 128, w[0], w[1], w[2], w[3]); sts128(vhs + 128 + 2048, w[4], w[5], w[6], w[7]); sts128(vhs + 128 + 4096, w[8], w[9], 0x00003f80u, 0u);
      }
#define FMAP(A, B, N, MODE, ACC, T0, NS)                                                      \
      {                                                                                       \
        float sc = st0.x * LOG2E;                                                             \
        _Pragma("unroll 1") for (int rr = 0; rr < 2; rr++) {                                  \
          float ep[20], en[20], ip, in;                                                       \
          fm_args(A, sc, ep, en);                                                             \
          _Pragma("unroll") for (int j = 0; j < 20; j++) A[j] = B[j];                         \
          sc = st1.x * LOG2E;                                                                 \
          pin(ep); pin(en); pin(A);                                                           \
          STEPR(N, MODE, ACC, T0 + NS * rr)                                                   \
          ip = fm_exp(ep);                                                                    \
          if (NS == 2) { pin(ep); STEPR(N, MODE, ACC, T0 + NS * rr + 1) }                     \
          in = fm_exp(en);                                                                    \
          if (on) fm_put(ep, ip, en, in, phs + rr * 128);                                     \
        }                                                                                     \
        fence_async_smem();                                                                   \
      }
      {
        FMAP(a, b, 104, 1, acc3, 21, 2)
        float kv0[12], kv1[12];
        nb_sync<NB_ALL, 256>();
        wg_fence();
#pragma unroll 1
        for (int s = 0; s < 8; s++) {
          const uint64_t da = dhi(2048, 0) + (uint32_t)(wg * (2 * PH_HS / 16) + s * 16), db = dhi(2048, 0) + (uint32_t)(wg * (2 * VH_HS / 16) + s * 16);
          wgmma<24, 1, 1, dlo(SB0 + PH_OFF, 128), dlo(SB0 + VH_OFF, 128)>(kv0, da, db, s);
          wgmma<24, 1, 1, dlo(SB0 + PH_OFF + PH_HS, 128), dlo(SB0 + VH_OFF + VH_HS, 128)>(kv1, da, db, s);
        }
        wg_commit();
        const int w = W & 3;
        float* ke = g_s.z[lds32(bars + B_EPOCH) & 1] + (uint32_t)((4 * c + 2 * wg) * 960 + (w * 16 + g) * 8 + 2 * q);
        keep(ke);
        STEP(104, 1, acc3, 25)
        pin(kv0); pin(kv1);
        if (w < 3) { red2(ke, kv0[0], kv0[1]); red2(ke + 960, kv1[0], kv1[1]); }
        STEP(104, 1, acc3, 26)
        if (w < 3) { red2(ke + 320, kv0[4], kv0[5]); red2(ke + 1280, kv1[4], kv1[5]); }
        STEP(104, 1, acc3, 27)
        if (w < 3) { red2(ke + 640, kv0[8], kv0[9]); red2(ke + 1600, kv1[8], kv1[9]); }
        STEP(104, 1, acc3, 28)
        if (w < 2) { red2(ke + 64, kv0[2], kv0[3]); red2(ke + 384, kv0[6], kv0[7]); red2(ke + 704, kv0[10], kv0[11]); }
        STEP(104, 1, acc3, 29)
        if (w < 2) { red2(ke + 1024, kv1[2], kv1[3]); red2(ke + 1344, kv1[6], kv1[7]); red2(ke + 1664, kv1[10], kv1[11]); }
        nb_arrive<NB_PUB + 3, 288>();

        float cc[20], ct[8];
        lds_cs(cc, csq + 44 * 8);
        lds_cs(ct, csq + 54 * 8);
        nb_sync<NB_ALL, 256>();
        STEP(160, 2, accg, 30, true)
        pin(acc3);
        {
          const float h0 = 0.5f * st0.x, h1 = 0.5f * st1.x;
          uint8_t* d = hth + (uint32_t)((192 + 3 * c) * 2048 + q * 4);
#pragma unroll
          for (int jj = 0; jj < 3; jj++) {
            const int j = 10 + jj;
            stg32(d + jj * 2048, pack2(silu_half(h0 * fmaf(ct[2 * jj], st0.y, acc3[4 * j])), silu_half(h0 * fmaf(ct[2 * jj + 1], st0.y, acc3[4 * j + 1]))));
            stg32(d + jj * 2048 + 128, pack2(silu_half(h1 * fmaf(ct[2 * jj], st1.y, acc3[4 * j + 2])), silu_half(h1 * fmaf(ct[2 * jj + 1], st1.y, acc3[4 * j + 3]))));
          }
        }
        nb_arrive<NB_PUB + 4, 288>();
        float a2[20], b2[20];
        fm_logits(acc3, cc, st0.y, st1.y, a2, b2);
        FMAP(a2, b2, 160, 2, accg, 31, 1)
      }
    }
    uint32_t peer;
    asm volatile("mapa.shared::cluster.u32 %0, %1, %2;" : "=r"(peer) : "r"(sb), "r"(ks ^ 1));
    {
      STEP(160, 2, accg, 33)
      if (wg) nb_sync<NB_WG0 + 1, 128>(); else nb_sync<NB_WG0, 128>();
      asm volatile("barrier.cluster.wait.aligned;" ::: "memory");
      float o0[12], o1[12], o2[12], o3[12];
      mbar_wait(bars + B_KVB, 0, nw);
      wg_fence();
#pragma unroll 1
      for (int s = 0; s < 3; s++) {
        const uint64_t da = DA(2, 13) + (uint32_t)(s * 256 + (s < 2 ? dlo(0, 2048) : 0)), db = dhi(768, 0) + (uint32_t)(s * 16);
        wgmma<24, 0, 1, dlo(SB0 + PH_OFF, 0), dlo(SB0 + VH_OFF, 128)>(o0, da, db, s);
        wgmma<24, 0, 1, dlo(SB0 + PH_OFF + PH_HS, 0), dlo(SB0 + VH_OFF + 2304, 128)>(o1, da, db, s);
        wgmma<24, 0, 1, dlo(SB0 + PH_OFF + 2 * PH_HS, 0), dlo(SB0 + VH_OFF + 2 * 2304, 128)>(o2, da, db, s);
        wgmma<24, 0, 1, dlo(SB0 + PH_OFF + 3 * PH_HS, 0), dlo(SB0 + VH_OFF + 3 * 2304, 128)>(o3, da, db, s);
      }
      wg_commit();
      STEP(160, 2, accg, T_O)
      pin(o0); pin(o1); pin(o2); pin(o3);
      if (lane == 0) mbar_arrive_remote(peer + BAR_OFF + B_XRDY);
      auto onorm = [&](const float (&e)[12], const float (&o)[12], uint32_t (&u)[10]) {
        const float e0 = rcpf(__shfl_sync(~0u, e[8], 2, 4) + 1e-6f), e1 = rcpf(__shfl_sync(~0u, e[10], 2, 4) + 1e-6f);
        const float f0 = rcpf(__shfl_sync(~0u, o[8], 0, 4) + 1e-6f), f1 = rcpf(__shfl_sync(~0u, o[10], 0, 4) + 1e-6f);
        u[0] = pack2(e[0] * e0, e[1] * e0); u[1] = pack2(e[2] * e1, e[3] * e1); u[2] = pack2(e[4] * e0, e[5] * e0); u[3] = pack2(e[6] * e1, e[7] * e1);
        u[4] = q < 2 ? pack2(e[8] * e0, e[9] * e0) : pack2(o[8] * f0, o[9] * f0);
        u[5] = q < 2 ? pack2(e[10] * e1, e[11] * e1) : pack2(o[10] * f1, o[11] * f1);
        u[6] = pack2(o[0] * f0, o[1] * f0); u[7] = pack2(o[2] * f1, o[3] * f1); u[8] = pack2(o[4] * f0, o[5] * f0); u[9] = pack2(o[6] * f1, o[7] * f1);
      };
      uint8_t* od = hth + (uint32_t)((216 + c * 10) * 2048 + q * 4);
      keep(od);
      uint32_t ua[10], ub[10];
      auto oput = [&](auto IC0) {
        constexpr int i0 = decltype(IC0)::value;
#pragma unroll
        for (int i = i0; i < i0 + 5; i++) stg32(od + (i >> 1) * 2048 + (i & 1) * 128, i < 10 ? ua[i] : ub[i - 10]);
      };
      onorm(o0, o1, ua);
      oput(IC<0>());
      STEP(160, 2, accg, T_O + 1)
      if (on) onorm(o2, o3, ub);
      oput(IC<5>());
      STEP(160, 2, accg, T_O + 2)
      oput(IC<10>());
      STEP(160, 2, accg, T_O + 3)
      oput(IC<15>());
      nb_arrive<NB_PUB + 5, 288>();
    }
#pragma unroll 1
    for (int t = T_O + 4; t < 43; t++) { STEPR(160, 2, accg, t) }
    STEP(160, 2, accg, 43, false, ks)

    float accs[80];
    const uint32_t xloc = sb + PH_OFF + tid * 16, xrem = peer + PH_OFF + tid * 16;
    auto xpack = [&](float (&acc)[80], uint32_t (&u)[20]) {
#pragma unroll
      for (int i = 0; i < 16; i++) u[i] = pack2(acc[32 + 2 * i], acc[33 + 2 * i]);
#pragma unroll
      for (int i = 0; i < 4; i++) u[16 + i] = pack2(ks ? acc[64 + 2 * i] : acc[72 + 2 * i], ks ? acc[65 + 2 * i] : acc[73 + 2 * i]);
#pragma unroll
      for (int i = 0; i < 8; i++) acc[32 + i] = ks ? acc[72 + i] : acc[64 + i];
    };
    const uint32_t xa = ((rb * 128 + W * 16 + (lane >> 3)) * D_ + 64 * (a0 + ks) + (lane & 7) * 8) * 2;
    const uint32_t xb = ((rb * 128 + W * 16 + (lane >> 1)) * D_ + 32 * pg + 16 * ks + (lane & 1) * 8) * 2;
    uint32_t u[20];
    const uint32_t xg = peer + BAR_OFF + B_XG, xs = peer + BAR_OFF + B_XS;
    STEP(160, 2, accs, 44, true)
    pin(accg);
    mbar_wait(bars + B_XRDY, 0, nw);
    xpack(accg, u);
    st_async4<0>(xrem, u[0], u[1], u[2], u[3], xg);
    STEP(160, 2, accs, 45)
    st_async4<4096>(xrem, u[4], u[5], u[6], u[7], xg); st_async4<8192>(xrem, u[8], u[9], u[10], u[11], xg);
    STEP(160, 2, accs, 46)
    st_async4<12288>(xrem, u[12], u[13], u[14], u[15], xg); st_async4<16384>(xrem, u[16], u[17], u[18], u[19], xg);
    STEP(160, 2, accs, 47)
    uint4 xr[5];
#pragma unroll
    for (int i = 0; i < 4; i++) xr[i] = ldg128((const char*)p.x + xa + i * 8 * D_);
    xr[4] = ldg128((const char*)p.x + xb);
    STEP(160, 2, accs, 48)
    mbar_wait(bars + B_XG, 0, nw);
#pragma unroll
    for (int i = 0; i < 5; i++) {
      const uint4 v = lds128(xloc + i * 4096);
      const uint32_t vv[4] = {v.x, v.y, v.z, v.w};
#pragma unroll
      for (int e = 0; e < 4; e++) { accg[8 * i + 2 * e] += bf_lo(vv[e]); accg[8 * i + 2 * e + 1] += bf_hi(vv[e]); }
    }
    wg_wait<0>();
    pin(accs); TRC(49);
    {
      xpack(accs, u);
      st_async4<20480>(xrem, u[0], u[1], u[2], u[3], xs); st_async4<24576>(xrem, u[4], u[5], u[6], u[7], xs); st_async4<28672>(xrem, u[8], u[9], u[10], u[11], xs);
      st_async4<32768>(xrem, u[12], u[13], u[14], u[15], xs); st_async4<36864>(xrem, u[16], u[17], u[18], u[19], xs);
      uint32_t gate[20], own[20];
      if (on) {
#pragma unroll
        for (int i = 0; i < 20; i++) gate[i] = pack2(silu_half(0.5f * accg[2 * i]), silu_half(0.5f * accg[2 * i + 1]));
      }
#pragma unroll
      for (int i = 0; i < 20; i++) { own[i] = hmul2bf(pack2(accs[2 * i], accs[2 * i + 1]), gate[i]); asm volatile("" : "+r"(own[i])); }
      const uint32_t ost = sb + VH_OFF + W * 2816;
      const uint32_t sta = ost + (lane & 15) * 176 + (lane >> 4) * 16;
      mbar_wait(bars + B_XS, 0, nw); TRC(50);
      uint4 rv[5];
#pragma unroll
      for (int b = 0; b < 5; b++) rv[b] = lds128(xloc + 20480 + b * 4096);
#pragma unroll
      for (int b = 0; b < 5; b++)
        asm volatile("stmatrix.sync.aligned.m8n8.x4.shared.b16 [%0], {%1,%2,%3,%4};" ::"r"(sta + b * 32), "r"(hfma2bf(rv[b].x, gate[4 * b], own[4 * b])),
                     "r"(hfma2bf(rv[b].y, gate[4 * b + 1], own[4 * b + 1])), "r"(hfma2bf(rv[b].z, gate[4 * b + 2], own[4 * b + 2])), "r"(hfma2bf(rv[b].w, gate[4 * b + 3], own[4 * b + 3])) : "memory");
      __syncwarp();
#pragma unroll
      for (int i = 0; i < 5; i++) {
        const uint4 v = lds128(i < 4 ? ost + (i * 4 + (lane >> 3)) * 176 + (lane & 7) * 16 : ost + (lane >> 1) * 176 + 128 + (lane & 1) * 16);
        stg128(i < 4 ? (char*)p.out + xa + i * 8 * D_ : (char*)p.out + xb, hadd2bf(xr[i].x, v.x), hadd2bf(xr[i].y, v.y), hadd2bf(xr[i].z, v.z), hadd2bf(xr[i].w, v.w));
      }
      TRC(51);
      if (pos == 0 && tid == 0 && nw != ~0u) g_s.flags[FL_EPOCH * 32] = lds32(bars + B_EPOCH) + 1;
    }
  }
}

typedef CUresult (*EncodeFn)(CUtensorMap*, CUtensorMapDataType, cuuint32_t, void*, const cuuint64_t*, const cuuint64_t*, const cuuint32_t*,
                             const cuuint32_t*, CUtensorMapInterleave, CUtensorMapSwizzle, CUtensorMapL2promotion, CUtensorMapFloatOOBfill);

static int make_map(EncodeFn enc, CUtensorMap* m, const void* base, int nd, const cuuint64_t* dims, const cuuint64_t* strides, const cuuint32_t* box,
                    CUtensorMapSwizzle sw = CU_TENSOR_MAP_SWIZZLE_128B) {
  const cuuint32_t es[5] = {1, 1, 1, 1, 1};
  return (int)enc(m, CU_TENSOR_MAP_DATA_TYPE_BFLOAT16, nd, const_cast<void*>(base), dims, strides, box, es, CU_TENSOR_MAP_INTERLEAVE_NONE,
                  sw, CU_TENSOR_MAP_L2_PROMOTION_L2_128B, CU_TENSOR_MAP_FLOAT_OOB_FILL_NONE);
}

extern "C" void kernel_launch(void* const* d_in, const int* in_sizes, int n_in, void* d_out, int out_size) {
  (void)in_sizes; (void)n_in; (void)out_size;
  void* fn = nullptr;
  cudaDriverEntryPointQueryResult qr;
  cudaGetDriverEntryPoint("cuTensorMapEncodeTiled", &fn, cudaEnableDefault, &qr);
  EncodeFn enc = (EncodeFn)fn;
  Params p;
  p.x = (const bf16*)d_in[0]; p.wqkv = (const bf16*)d_in[1]; p.wphi = (const bf16*)d_in[2]; p.wo = (const bf16*)d_in[3];
  p.w1 = (const bf16*)d_in[5]; p.w2 = (const bf16*)d_in[6]; p.out = (bf16*)d_out; p.one = 1;
  for (int i = 0; i < 14; i++) { p.dsw[i] = dhi(1024, 1); p.dns[i] = dhi(128, 0); }
  for (int cl = 0; cl < 64; cl++) {
    int grp, t;
    if (cl < 4) { grp = 15; t = cl; }
    else if (cl < 36) { grp = (cl - 4) & 7; t = (cl - 4) >> 3; }
    else { grp = 8 + (cl - 36) % 7; t = (cl - 36) / 7; }
    p.tile[cl] = grp * 8 + t * 2;
  }
  int err = 0;
  void* scr = nullptr;
  cudaGetSymbolAddress(&scr, g_s);
  { const cuuint64_t d[3] = {64, 33, 640}, s[2] = {128, WP_KG}; const cuuint32_t b2[3] = {64, 20, 8}, b3[3] = {64, 13, 8};
    err |= make_map(enc, &p.mWp2, ((Scratch*)scr)->wp, 3, d, s, b2, CU_TENSOR_MAP_SWIZZLE_NONE); err |= make_map(enc, &p.mWp3, ((Scratch*)scr)->wp, 3, d, s, b3, CU_TENSOR_MAP_SWIZZLE_NONE); }
  { const cuuint64_t d[2] = {640, 2048}, s[1] = {1280}; const cuuint32_t b[2] = {64, 128}; err |= make_map(enc, &p.mX, p.x, 2, d, s, b); }
  { const cuuint64_t d[3] = {64, 640, 27}, s[2] = {3456, 128}; const cuuint32_t b[3] = {64, 64, 3}; err |= make_map(enc, &p.mW1, p.w1, 3, d, s, b);
    const cuuint32_t bs[3] = {64, 40, 3}; err |= make_map(enc, &p.mW1s, p.w1, 3, d, s, bs); }
  { const cuuint64_t d[2] = {1728, 640}, s[1] = {3456}; const cuuint32_t b[2] = {24, 40}; err |= make_map(enc, &p.mWts, p.w1, 2, d, s, b, CU_TENSOR_MAP_SWIZZLE_NONE); }
  { const cuuint64_t d[3] = {640, 640, 3}, s[2] = {3840, 1280}; const cuuint32_t b[3] = {80, 40, 3}; err |= make_map(enc, &p.mQs, p.wqkv, 3, d, s, b, CU_TENSOR_MAP_SWIZZLE_NONE); }
  { const cuuint64_t d[5] = {64, 8, 216, 1, 10}, s[4] = {1280, 10240, 1280, 128}; const cuuint32_t b[5] = {64, 8, 8, 1, 1}; err |= make_map(enc, &p.mW2n, p.w2, 5, d, s, b); }
  { const cuuint64_t d[5] = {64, 2, 216, 4, 10}, s[4] = {1280, 10240, 2560, 128}; const cuuint32_t b[5] = {64, 2, 8, 4, 1}; err |= make_map(enc, &p.mW2a, p.w2, 5, d, s, b); }
  { const cuuint64_t d[5] = {64, 8, 80, 1, 10}, s[4] = {1280, 10240, 1280, 128}; const cuuint32_t b[5] = {64, 8, 8, 1, 1}; err |= make_map(enc, &p.mWoa, p.wo, 5, d, s, b); }
  if (err) return;
  cudaFuncSetAttribute(fused_kernel, cudaFuncAttributeMaxDynamicSharedMemorySize, SMEM_BYTES);
  fused_kernel<<<128, NTHR, SMEM_BYTES>>>(p);
}
```

```cpp
#include <cuda_runtime.h>
#include <cuda_bf16.h>
#include <cuda.h>
#include <stdint.h>
#include <type_traits>
#include <stddef.h>

typedef __nv_bfloat16 bf16;

template<int TA,int TB,uint32_t IA,uint32_t IB> __device__ __forceinline__ void wgmma_n24(float (&d)[12], uint64_t a, uint64_t b, int sd) {
  asm volatile("{\n.reg .pred p;\n.reg .b64 da, db;\nsetp.ne.b32 p, %14, 0;\n"
    "add.s64 da, %12, %17;\nadd.s64 db, %13, %18;\n"
    "wgmma.mma_async.sync.aligned.m64n24k16.f32.bf16.bf16 {%0,%1,%2,%3,%4,%5,%6,%7,%8,%9,%10,%11}, da, db, p, 1, 1, %15, %16;\n}\n"
    : "+f"(d[0]),"+f"(d[1]),"+f"(d[2]),"+f"(d[3]),"+f"(d[4]),"+f"(d[5]),"+f"(d[6]),"+f"(d[7]),"+f"(d[8]),"+f"(d[9]),"+f"(d[10]),"+f"(d[11])
    : "l"(a), "l"(b), "r"(sd), "n"(TA), "n"(TB), "n"(IA), "n"(IB));
}

template<int TA,int TB,uint32_t IA,uint32_t IB> __device__ __forceinline__ void wgmma_n48(float (&d)[24], uint64_t a, uint64_t b, int sd) {
  asm volatile("{\n.reg .pred p;\n.reg .b64 da, db;\nsetp.ne.b32 p, %26, 0;\n"
    "add.s64 da, %24, %29;\nadd.s64 db, %25, %30;\n"
    "wgmma.mma_async.sync.aligned.m64n48k16.f32.bf16.bf16 {%0,%1,%2,%3,%4,%5,%6,%7,%8,%9,%10,%11,%12,%13,%14,%15,%16,%17,%18,%19,%20,%21,%22,%23}, da, db, p, 1, 1, %27, %28;\n}\n"
    : "+f"(d[0]),"+f"(d[1]),"+f"(d[2]),"+f"(d[3]),"+f"(d[4]),"+f"(d[5]),"+f"(d[6]),"+f"(d[7]),"+f"(d[8]),"+f"(d[9]),"+f"(d[10]),"+f"(d[11]),"+f"(d[12]),"+f"(d[13]),"+f"(d[14]),"+f"(d[15]),"+f"(d[16]),"+f"(d[17]),"+f"(d[18]),"+f"(d[19]),"+f"(d[20]),"+f"(d[21]),"+f"(d[22]),"+f"(d[23])
    : "l"(a), "l"(b), "r"(sd), "n"(TA), "n"(TB), "n"(IA), "n"(IB));
}

template<int TA,int TB,uint32_t IA,uint32_t IB> __device__ __forceinline__ void wgmma_n80(float (&d)[40], uint64_t a, uint64_t b, int sd) {
  asm volatile("{\n.reg .pred p;\n.reg .b64 da, db;\nsetp.ne.b32 p, %42, 0;\n"
    "add.s64 da, %40, %45;\nadd.s64 db, %41, %46;\n"
    "wgmma.mma_async.sync.aligned.m64n80k16.f32.bf16.bf16 {%0,%1,%2,%3,%4,%5,%6,%7,%8,%9,%10,%11,%12,%13,%14,%15,%16,%17,%18,%19,%20,%21,%22,%23,%24,%25,%26,%27,%28,%29,%30,%31,%32,%33,%34,%35,%36,%37,%38,%39}, da, db, p, 1, 1, %43, %44;\n}\n"
    : "+f"(d[0]),"+f"(d[1]),"+f"(d[2]),"+f"(d[3]),"+f"(d[4]),"+f"(d[5]),"+f"(d[6]),"+f"(d[7]),"+f"(d[8]),"+f"(d[9]),"+f"(d[10]),"+f"(d[11]),"+f"(d[12]),"+f"(d[13]),"+f"(d[14]),"+f"(d[15]),"+f"(d[16]),"+f"(d[17]),"+f"(d[18]),"+f"(d[19]),"+f"(d[20]),"+f"(d[21]),"+f"(d[22]),"+f"(d[23]),"+f"(d[24]),"+f"(d[25]),"+f"(d[26]),"+f"(d[27]),"+f"(d[28]),"+f"(d[29]),"+f"(d[30]),"+f"(d[31]),"+f"(d[32]),"+f"(d[33]),"+f"(d[34]),"+f"(d[35]),"+f"(d[36]),"+f"(d[37]),"+f"(d[38]),"+f"(d[39])
    : "l"(a), "l"(b), "r"(sd), "n"(TA), "n"(TB), "n"(IA), "n"(IB));
}

template<int TA,int TB,uint32_t IA,uint32_t IB> __device__ __forceinline__ void wgmma_n104(float (&d)[52], uint64_t a, uint64_t b, int sd) {
  asm volatile("{\n.reg .pred p;\n.reg .b64 da, db;\nsetp.ne.b32 p, %54, 0;\n"
    "add.s64 da, %52, %57;\nadd.s64 db, %53, %58;\n"
    "wgmma.mma_async.sync.aligned.m64n104k16.f32.bf16.bf16 {%0,%1,%2,%3,%4,%5,%6,%7,%8,%9,%10,%11,%12,%13,%14,%15,%16,%17,%18,%19,%20,%21,%22,%23,%24,%25,%26,%27,%28,%29,%30,%31,%32,%33,%34,%35,%36,%37,%38,%39,%40,%41,%42,%43,%44,%45,%46,%47,%48,%49,%50,%51}, da, db, p, 1, 1, %55, %56;\n}\n"
    : "+f"(d[0]),"+f"(d[1]),"+f"(d[2]),"+f"(d[3]),"+f"(d[4]),"+f"(d[5]),"+f"(d[6]),"+f"(d[7]),"+f"(d[8]),"+f"(d[9]),"+f"(d[10]),"+f"(d[11]),"+f"(d[12]),"+f"(d[13]),"+f"(d[14]),"+f"(d[15]),"+f"(d[16]),"+f"(d[17]),"+f"(d[18]),"+f"(d[19]),"+f"(d[20]),"+f"(d[21]),"+f"(d[22]),"+f"(d[23]),"+f"(d[24]),"+f"(d[25]),"+f"(d[26]),"+f"(d[27]),"+f"(d[28]),"+f"(d[29]),"+f"(d[30]),"+f"(d[31]),"+f"(d[32]),"+f"(d[33]),"+f"(d[34]),"+f"(d[35]),"+f"(d[36]),"+f"(d[37]),"+f"(d[38]),"+f"(d[39]),"+f"(d[40]),"+f"(d[41]),"+f"(d[42]),"+f"(d[43]),"+f"(d[44]),"+f"(d[45]),"+f"(d[46]),"+f"(d[47]),"+f"(d[48]),"+f"(d[49]),"+f"(d[50]),"+f"(d[51])
    : "l"(a), "l"(b), "r"(sd), "n"(TA), "n"(TB), "n"(IA), "n"(IB));
}

template<int TA,int TB,uint32_t IA,uint32_t IB> __device__ __forceinline__ void wgmma_n160(float (&d)[80], uint64_t a, uint64_t b, int sd) {
  asm volatile("{\n.reg .pred p;\n.reg .b64 da, db;\nsetp.ne.b32 p, %82, 0;\n"
    "add.s64 da, %80, %85;\nadd.s64 db, %81, %86;\n"
    "wgmma.mma_async.sync.aligned.m64n160k16.f32.bf16.bf16 {%0,%1,%2,%3,%4,%5,%6,%7,%8,%9,%10,%11,%12,%13,%14,%15,%16,%17,%18,%19,%20,%21,%22,%23,%24,%25,%26,%27,%28,%29,%30,%31,%32,%33,%34,%35,%36,%37,%38,%39,%40,%41,%42,%43,%44,%45,%46,%47,%48,%49,%50,%51,%52,%53,%54,%55,%56,%57,%58,%59,%60,%61,%62,%63,%64,%65,%66,%67,%68,%69,%70,%71,%72,%73,%74,%75,%76,%77,%78,%79}, da, db, p, 1, 1, %83, %84;\n}\n"
    : "+f"(d[0]),"+f"(d[1]),"+f"(d[2]),"+f"(d[3]),"+f"(d[4]),"+f"(d[5]),"+f"(d[6]),"+f"(d[7]),"+f"(d[8]),"+f"(d[9]),"+f"(d[10]),"+f"(d[11]),"+f"(d[12]),"+f"(d[13]),"+f"(d[14]),"+f"(d[15]),"+f"(d[16]),"+f"(d[17]),"+f"(d[18]),"+f"(d[19]),"+f"(d[20]),"+f"(d[21]),"+f"(d[22]),"+f"(d[23]),"+f"(d[24]),"+f"(d[25]),"+f"(d[26]),"+f"(d[27]),"+f"(d[28]),"+f"(d[29]),"+f"(d[30]),"+f"(d[31]),"+f"(d[32]),"+f"(d[33]),"+f"(d[34]),"+f"(d[35]),"+f"(d[36]),"+f"(d[37]),"+f"(d[38]),"+f"(d[39]),"+f"(d[40]),"+f"(d[41]),"+f"(d[42]),"+f"(d[43]),"+f"(d[44]),"+f"(d[45]),"+f"(d[46]),"+f"(d[47]),"+f"(d[48]),"+f"(d[49]),"+f"(d[50]),"+f"(d[51]),"+f"(d[52]),"+f"(d[53]),"+f"(d[54]),"+f"(d[55]),"+f"(d[56]),"+f"(d[57]),"+f"(d[58]),"+f"(d[59]),"+f"(d[60]),"+f"(d[61]),"+f"(d[62]),"+f"(d[63]),"+f"(d[64]),"+f"(d[65]),"+f"(d[66]),"+f"(d[67]),"+f"(d[68]),"+f"(d[69]),"+f"(d[70]),"+f"(d[71]),"+f"(d[72]),"+f"(d[73]),"+f"(d[74]),"+f"(d[75]),"+f"(d[76]),"+f"(d[77]),"+f"(d[78]),"+f"(d[79])
    : "l"(a), "l"(b), "r"(sd), "n"(TA), "n"(TB), "n"(IA), "n"(IB));
}

template<int TA,int TB,uint32_t IA,uint32_t IB> __device__ __forceinline__ void wgmma_n192(float (&d)[96], uint64_t a, uint64_t b, int sd) {
  asm volatile("{\n.reg .pred p;\n.reg .b64 da, db;\nsetp.ne.b32 p, %98, 0;\n"
    "add.s64 da, %96, %101;\nadd.s64 db, %97, %102;\n"
    "wgmma.mma_async.sync.aligned.m64n192k16.f32.bf16.bf16 {%0,%1,%2,%3,%4,%5,%6,%7,%8,%9,%10,%11,%12,%13,%14,%15,%16,%17,%18,%19,%20,%21,%22,%23,%24,%25,%26,%27,%28,%29,%30,%31,%32,%33,%34,%35,%36,%37,%38,%39,%40,%41,%42,%43,%44,%45,%46,%47,%48,%49,%50,%51,%52,%53,%54,%55,%56,%57,%58,%59,%60,%61,%62,%63,%64,%65,%66,%67,%68,%69,%70,%71,%72,%73,%74,%75,%76,%77,%78,%79,%80,%81,%82,%83,%84,%85,%86,%87,%88,%89,%90,%91,%92,%93,%94,%95}, da, db, p, 1, 1, %99, %100;\n}\n"
    : "+f"(d[0]),"+f"(d[1]),"+f"(d[2]),"+f"(d[3]),"+f"(d[4]),"+f"(d[5]),"+f"(d[6]),"+f"(d[7]),"+f"(d[8]),"+f"(d[9]),"+f"(d[10]),"+f"(d[11]),"+f"(d[12]),"+f"(d[13]),"+f"(d[14]),"+f"(d[15]),"+f"(d[16]),"+f"(d[17]),"+f"(d[18]),"+f"(d[19]),"+f"(d[20]),"+f"(d[21]),"+f"(d[22]),"+f"(d[23]),"+f"(d[24]),"+f"(d[25]),"+f"(d[26]),"+f"(d[27]),"+f"(d[28]),"+f"(d[29]),"+f"(d[30]),"+f"(d[31]),"+f"(d[32]),"+f"(d[33]),"+f"(d[34]),"+f"(d[35]),"+f"(d[36]),"+f"(d[37]),"+f"(d[38]),"+f"(d[39]),"+f"(d[40]),"+f"(d[41]),"+f"(d[42]),"+f"(d[43]),"+f"(d[44]),"+f"(d[45]),"+f"(d[46]),"+f"(d[47]),"+f"(d[48]),"+f"(d[49]),"+f"(d[50]),"+f"(d[51]),"+f"(d[52]),"+f"(d[53]),"+f"(d[54]),"+f"(d[55]),"+f"(d[56]),"+f"(d[57]),"+f"(d[58]),"+f"(d[59]),"+f"(d[60]),"+f"(d[61]),"+f"(d[62]),"+f"(d[63]),"+f"(d[64]),"+f"(d[65]),"+f"(d[66]),"+f"(d[67]),"+f"(d[68]),"+f"(d[69]),"+f"(d[70]),"+f"(d[71]),"+f"(d[72]),"+f"(d[73]),"+f"(d[74]),"+f"(d[75]),"+f"(d[76]),"+f"(d[77]),"+f"(d[78]),"+f"(d[79]),"+f"(d[80]),"+f"(d[81]),"+f"(d[82]),"+f"(d[83]),"+f"(d[84]),"+f"(d[85]),"+f"(d[86]),"+f"(d[87]),"+f"(d[88]),"+f"(d[89]),"+f"(d[90]),"+f"(d[91]),"+f"(d[92]),"+f"(d[93]),"+f"(d[94]),"+f"(d[95])
    : "l"(a), "l"(b), "r"(sd), "n"(TA), "n"(TB), "n"(IA), "n"(IB));
}

template<int N,int TA,int TB,uint32_t IA,uint32_t IB> __device__ __forceinline__ void wgmma(float (&d)[N/2], uint64_t a, uint64_t b, int sd) {
  if constexpr (N==24) wgmma_n24<TA,TB,IA,IB>(d,a,b,sd);
  if constexpr (N==48) wgmma_n48<TA,TB,IA,IB>(d,a,b,sd);
  if constexpr (N==80) wgmma_n80<TA,TB,IA,IB>(d,a,b,sd);
  if constexpr (N==104) wgmma_n104<TA,TB,IA,IB>(d,a,b,sd);
  if constexpr (N==160) wgmma_n160<TA,TB,IA,IB>(d,a,b,sd);
  if constexpr (N==192) wgmma_n192<TA,TB,IA,IB>(d,a,b,sd);
}

#define T_O 37
#define GB 0
#define HSM 3
#define VTAB 0
#define XA 8
#define XB 6
#define QOLD 1
#define OPAT 0
#define NODRAIN 0
#define EWMASK 0x1FF000ull
#define XMASK 0x3F0FC3FFu
#define TF 3
#define SDLY 0
#define MRG 0
#define XRP 2
#define OW44 0
#define NTHR 384
namespace {

constexpr int S_ = 2048, D_ = 640;
constexpr int CS_N = 464;
constexpr int KV_FLOATS = 32 * 1152;
static_assert(KV_FLOATS + 8 * CS_N <= 128 * 80 * 4, "z");
constexpr int WP_KG = 33 * 128;

constexpr int SLOT = 40960, NSLOT = 4;
constexpr int PH_OFF = NSLOT * SLOT;
constexpr int PH_HS = 10272;
constexpr int VH_OFF = PH_OFF + 4 * PH_HS;
constexpr int VH_HS = 6176;
constexpr int CS_OFF = VH_OFF + 4 * VH_HS;
constexpr int CS_QS = 464;
constexpr int BAR_OFF = CS_OFF + 4 * CS_QS;
constexpr int SMEM_BYTES = BAR_OFF + 176;
static_assert(SMEM_BYTES <= 232448, "smem");
constexpr uint32_t SB0 = 0x400;
constexpr int B_FULL = 0, B_EMPTY = 32, B_CS = 64, B_KVB = 72, B_XRDY = 80, B_XG = 88, B_XS = 96, B_SLAB = 104, B_SLAB2 = 112, B_DEP = 120, B_EPOCH = 168;
constexpr int SL_W1 = PH_OFF, SL_QKV = SL_W1 + 15360, SL_WT = SL_QKV + 19200, SL_PHI = SL_WT + 1920, SL_ST = SL_PHI + 3200;
constexpr int EX_A = PH_OFF, EX_B = PH_OFF + 2048;

constexpr int NB_PUB = 1, NB_ALL = 11, NB_WG0 = 8;

constexpr int FL_EPOCH = 128, FL_N = 136;

struct Params {
  CUtensorMap mX, mW1, mW1s, mWts, mQs, mWp2, mWp3, mW2a, mW2n, mW2h;
  const bf16 *x, *wqkv, *wphi, *w1, *w2, *wo;
  bf16* out;
  uint64_t dsw[15], dns[15];
  uint16_t vrow[128];
  int tile[64];
  int one;
};

struct Scratch {
  unsigned flags[FL_N * 32];
  float2 stats[S_];
  float z[2][128 * 80 * 4];
  uint8_t wp[8 * 80 * WP_KG];
  uint8_t wx[2 * 27 * 8192];
  uint8_t wo[8 * 80 * 1280];
  uint8_t ho[16 * 37 * 16384];
};

}

__device__ __align__(1024) Scratch g_s;
#define TR(role, idx)
#define TRC(idx)

namespace {

__device__ __forceinline__ uint32_t smem_u32(const void* p) { return (uint32_t)__cvta_generic_to_shared(p); }
__device__ __forceinline__ void mbar_init(uint32_t b, int c) { asm volatile("mbarrier.init.shared::cta.b64 [%0], %1;" ::"r"(b), "r"(c) : "memory"); }
__device__ __forceinline__ void mbar_expect(uint32_t b, int bytes) { asm volatile("mbarrier.arrive.expect_tx.shared::cta.b64 _, [%0], %1;" ::"r"(b), "r"(bytes) : "memory"); }
__device__ __forceinline__ void mbar_arrive(uint32_t b) { asm volatile("mbarrier.arrive.shared::cta.b64 _, [%0];" ::"r"(b) : "memory"); }
__device__ __forceinline__ void mbar_arrive_remote(uint32_t rb) { asm volatile("mbarrier.arrive.relaxed.cluster.shared::cluster.b64 _, [%0];" ::"r"(rb) : "memory"); }
__device__ __forceinline__ void mbar_wait_long(uint32_t b, uint32_t ph) {
  asm volatile("{\n.reg .pred p, c;\n.reg .u32 n;\nmov.u32 n, 0;\nWL:\n"
               "mbarrier.try_wait.parity.shared::cta.b64 p, [%0], %1;\n"
               "add.u32 n, n, 1;\nsetp.lt.and.u32 c, n, 100000, !p;\n@c bra WL;\n}" ::"r"(b), "r"(ph) : "memory");
}
__device__ __forceinline__ void mbar_wait(uint32_t b, uint32_t ph, uint32_t& n) {
  asm volatile("{\n.reg .pred p;\nWL:\nmbarrier.try_wait.parity.shared::cta.b64 p, [%1], %2;\nadd.u32 %0, %0, 1;\n@!p bra WL;\n}" : "+r"(n) : "r"(b), "r"(ph) : "memory");
}
__device__ __forceinline__ unsigned ld_rlx(const unsigned* p) { unsigned v; asm volatile("ld.relaxed.gpu.global.u32 %0, [%1];" : "=r"(v) : "l"(p) : "memory"); return v; }
__device__ __forceinline__ void flag_wait(const unsigned* f, unsigned target) {
  asm volatile("{\n.reg .pred p;\n.reg .u32 n;\n.reg .s32 v;\nmov.u32 n, 0;\nFL:\n"
               "ld.relaxed.gpu.global.s32 v, [%0];\nsub.s32 v, v, %1;\nadd.u32 n, n, 1;\n"
               "setp.lt.s32 p, v, 0;\nsetp.lt.and.u32 p, n, 40000, p;\n@p bra FL;\n}" ::"l"(f), "r"(target) : "memory");
}
__device__ __forceinline__ bool elect_one() {
  uint32_t e;
  asm volatile("{\n.reg .pred p;\nelect.sync _|p, 0xffffffff;\nselp.u32 %0, 1, 0, p;\n}" : "=r"(e));
  return e != 0;
}
__device__ __forceinline__ void fence_async_glob() { asm volatile("fence.proxy.async.global;" ::: "memory"); }
__device__ __forceinline__ void fence_async_smem() { asm volatile("fence.proxy.async.shared::cta;" ::: "memory"); }
template <int ID, int N> __device__ __forceinline__ void nb_sync() { asm volatile("bar.sync %0, %1;" ::"n"(ID), "n"(N) : "memory"); }
template <int ID, int N> __device__ __forceinline__ void nb_arrive() { asm volatile("bar.arrive %0, %1;" ::"n"(ID), "n"(N) : "memory"); }

__device__ __forceinline__ void tma1d(uint32_t dst, const void* src, int bytes, uint32_t bar) {
  asm volatile("cp.async.bulk.shared::cluster.global.mbarrier::complete_tx::bytes [%0], [%1], %2, [%3];" ::"r"(dst), "l"(src), "r"(bytes), "r"(bar) : "memory");
}
__device__ __forceinline__ void tma2d(uint32_t dst, const CUtensorMap* m, int c0, int c1, uint32_t bar) {
  asm volatile("cp.async.bulk.tensor.2d.shared::cluster.global.mbarrier::complete_tx::bytes [%0], [%1, {%3,%4}], [%2];" ::"r"(dst), "l"(m), "r"(bar), "r"(c0), "r"(c1) : "memory");
}
__device__ __forceinline__ void tma3d(uint32_t dst, const CUtensorMap* m, int c1, int c2, uint32_t bar) {
  asm volatile("cp.async.bulk.tensor.3d.shared::cluster.global.mbarrier::complete_tx::bytes [%0], [%1, {%5,%3,%4}], [%2];" ::"r"(dst), "l"(m), "r"(bar), "r"(c1), "r"(c2), "r"(0) : "memory");
}
__device__ __forceinline__ void tma3d0(uint32_t dst, const CUtensorMap* m, int c0, int c1, uint32_t bar) {
  asm volatile("cp.async.bulk.tensor.3d.shared::cluster.global.mbarrier::complete_tx::bytes [%0], [%1, {%3,%4,%5}], [%2];" ::"r"(dst), "l"(m), "r"(bar), "r"(c0), "r"(c1), "r"(0) : "memory");
}
__device__ __forceinline__ void tma5d(uint32_t dst, const CUtensorMap* m, int c2, int c4, uint32_t bar) {
  asm volatile("cp.async.bulk.tensor.5d.shared::cluster.global.mbarrier::complete_tx::bytes [%0], [%1, {%5,%5,%3,%5,%4}], [%2];" ::"r"(dst), "l"(m), "r"(bar), "r"(c2), "r"(c4), "r"(0) : "memory");
}
__device__ __forceinline__ void prefetch_map(const CUtensorMap* m) { asm volatile("prefetch.tensormap [%0];" ::"l"(m) : "memory"); }
__device__ __forceinline__ void prefetch_l2(const void* p) { asm volatile("prefetch.global.L2 [%0];" ::"l"(p) : "memory"); }

__host__ __device__ constexpr uint32_t dlo(uint32_t addr, uint32_t lbo) { return (addr >> 4) + ((lbo >> 4) << 16); }
__host__ __device__ constexpr uint64_t dhi(uint32_t sbo, uint32_t sw) { return (uint64_t)((sbo >> 4) | (sw << 30)) << 32; }
__device__ __forceinline__ void wg_fence() { asm volatile("wgmma.fence.sync.aligned;" ::: "memory"); }
__device__ __forceinline__ void wg_commit() { asm volatile("wgmma.commit_group.sync.aligned;" ::: "memory"); }
template <int N> __device__ __forceinline__ void wg_wait() { asm volatile("wgmma.wait_group.sync.aligned %0;" ::"n"(N) : "memory"); }
template <int I> using IC = std::integral_constant<int, I>;
template <class T> __device__ __forceinline__ void keep(T*& p) { asm volatile("" : "+l"(p)); }
__device__ __forceinline__ void keep(float& a, float& b) { asm volatile("" : "+f"(a), "+f"(b)); }
template <int N> __device__ __forceinline__ void pinu(uint32_t (&d)[N]) {
#pragma unroll
  for (int i = 0; i < N; i++) asm volatile("" : "+r"(d[i])::"memory");
}
template <int N> __device__ __forceinline__ void pin(float (&d)[N]) {
#pragma unroll
  for (int i = 0; i < N; i++) asm volatile("" : "+f"(d[i])::"memory");
}

__device__ __forceinline__ uint32_t pack2(float lo, float hi) { uint32_t r; asm("cvt.rn.bf16x2.f32 %0, %1, %2;" : "=r"(r) : "f"(hi), "f"(lo)); return r; }
__device__ __forceinline__ float ex2f(float x) { float y; asm("ex2.approx.ftz.f32 %0, %1;" : "=f"(y) : "f"(x)); return y; }
__device__ __forceinline__ float rcpf(float x) { float y; asm("rcp.approx.ftz.f32 %0, %1;" : "=f"(y) : "f"(x)); return y; }
__device__ __forceinline__ float tanhf_(float x) { float y; asm("tanh.approx.f32 %0, %1;" : "=f"(y) : "f"(x)); return y; }
__device__ __forceinline__ float silu_half(float y) { return fmaf(y, tanhf_(y), y); }

__device__ __forceinline__ uint4 ldg128(const void* p) { uint4 v; asm volatile("ld.global.nc.v4.u32 {%0,%1,%2,%3}, [%4];" : "=r"(v.x), "=r"(v.y), "=r"(v.z), "=r"(v.w) : "l"(p)); return v; }
__device__ __forceinline__ void stg128(void* p, uint32_t a, uint32_t b, uint32_t c, uint32_t d) { asm volatile("st.global.v4.u32 [%0], {%1,%2,%3,%4};" ::"l"(p), "r"(a), "r"(b), "r"(c), "r"(d) : "memory"); }
__device__ __forceinline__ void stg64(void* p, uint32_t a, uint32_t b) { asm volatile("st.global.v2.u32 [%0], {%1,%2};" ::"l"(p), "r"(a), "r"(b) : "memory"); }
__device__ __forceinline__ void stg32(void* p, uint32_t a) { asm volatile("st.global.u32 [%0], %1;" ::"l"(p), "r"(a) : "memory"); }
__device__ __forceinline__ void sts128(uint32_t p, uint32_t a, uint32_t b, uint32_t c, uint32_t d) { asm volatile("st.shared.v4.u32 [%0], {%1,%2,%3,%4};" ::"r"(p), "r"(a), "r"(b), "r"(c), "r"(d) : "memory"); }
__device__ __forceinline__ void sts32(uint32_t p, uint32_t a) { asm volatile("st.shared.u32 [%0], %1;" ::"r"(p), "r"(a) : "memory"); }
__device__ __forceinline__ float4 lds128f(uint32_t p) { float4 v; asm volatile("ld.shared.v4.f32 {%0,%1,%2,%3}, [%4];" : "=f"(v.x), "=f"(v.y), "=f"(v.z), "=f"(v.w) : "r"(p) : "memory"); return v; }
__device__ __forceinline__ uint4 lds128(uint32_t p) { uint4 v; asm volatile("ld.shared.v4.u32 {%0,%1,%2,%3}, [%4];" : "=r"(v.x), "=r"(v.y), "=r"(v.z), "=r"(v.w) : "r"(p) : "memory"); return v; }
__device__ __forceinline__ void red1(float* p, float a) { asm volatile("red.relaxed.gpu.global.add.f32 [%0], %1;" ::"l"(p), "f"(a) : "memory"); }
__device__ __forceinline__ void red2(float* p, float a, float b) { asm volatile("red.relaxed.gpu.global.add.v2.f32 [%0], {%1,%2};" ::"l"(p), "f"(a), "f"(b) : "memory"); }
template <int OFF>
__device__ __forceinline__ void st_async4(uint32_t ra, uint32_t a, uint32_t b, uint32_t c, uint32_t d, uint32_t rbar) {
  asm volatile("st.async.weak.shared::cluster.mbarrier::complete_tx::bytes.v4.b32 [%0+%6], {%1,%2,%3,%4}, [%5];" ::"r"(ra), "r"(a), "r"(b), "r"(c), "r"(d), "r"(rbar), "n"(OFF) : "memory");
}
__device__ __forceinline__ float bf_lo(uint32_t v) { return __uint_as_float(v << 16); }
__device__ __forceinline__ float bf_hi(uint32_t v) { return __uint_as_float(v & 0xffff0000u); }
__device__ __forceinline__ uint32_t lds32(uint32_t p) { uint32_t v; asm volatile("ld.shared.u32 %0, [%1];" : "=r"(v) : "r"(p) : "memory"); return v; }
__device__ __forceinline__ uint2 lds64(uint32_t p) { uint2 v; asm volatile("ld.shared.v2.u32 {%0,%1}, [%2];" : "=r"(v.x), "=r"(v.y) : "r"(p) : "memory"); return v; }
__device__ __forceinline__ uint4 ldsm4t(uint32_t p) { uint4 v; asm volatile("ldmatrix.sync.aligned.m8n8.x4.trans.shared.b16 {%0,%1,%2,%3}, [%4];" : "=r"(v.x), "=r"(v.y), "=r"(v.z), "=r"(v.w) : "r"(p) : "memory"); return v; }
__device__ __forceinline__ uint32_t movtrans(uint32_t a) { uint32_t d; asm volatile("movmatrix.sync.aligned.m8n8.trans.b16 %0, %1;" : "=r"(d) : "r"(a)); return d; }
__device__ __forceinline__ void mma16816(float (&d)[4], uint32_t a0, uint32_t a1, uint32_t a2, uint32_t a3, uint32_t b0, uint32_t b1) {
  asm volatile("mma.sync.aligned.m16n8k16.row.col.f32.bf16.bf16.f32 {%0,%1,%2,%3}, {%4,%5,%6,%7}, {%8,%9}, {%10,%10,%10,%10};"
               : "=f"(d[0]), "=f"(d[1]), "=f"(d[2]), "=f"(d[3]) : "r"(a0), "r"(a1), "r"(a2), "r"(a3), "r"(b0), "r"(b1), "f"(0.f));
}
__device__ __forceinline__ void mma16816a(float (&d)[4], uint32_t a0, uint32_t a1, uint32_t a2, uint32_t a3, uint32_t b0, uint32_t b1) {
  asm volatile("mma.sync.aligned.m16n8k16.row.col.f32.bf16.bf16.f32 {%0,%1,%2,%3}, {%4,%5,%6,%7}, {%8,%9}, {%0,%1,%2,%3};"
               : "+f"(d[0]), "+f"(d[1]), "+f"(d[2]), "+f"(d[3]) : "r"(a0), "r"(a1), "r"(a2), "r"(a3), "r"(b0), "r"(b1));
}
__device__ __forceinline__ void mma1688(float (&d)[4], uint32_t a0, uint32_t a1, uint32_t b0) {
  asm volatile("mma.sync.aligned.m16n8k8.row.col.f32.bf16.bf16.f32 {%0,%1,%2,%3}, {%4,%5}, {%6}, {%0,%1,%2,%3};"
               : "+f"(d[0]), "+f"(d[1]), "+f"(d[2]), "+f"(d[3]) : "r"(a0), "r"(a1), "r"(b0));
}
__device__ __forceinline__ uint32_t hadd2bf(uint32_t a, uint32_t b) { uint32_t d; asm("add.rn.bf16x2 %0, %1, %2;" : "=r"(d) : "r"(a), "r"(b)); return d; }
__device__ __forceinline__ uint32_t hfma2bf(uint32_t a, uint32_t b, uint32_t c) { uint32_t d; asm("fma.rn.bf16x2 %0, %1, %2, %3;" : "=r"(d) : "r"(a), "r"(b), "r"(c)); return d; }
__device__ __forceinline__ uint32_t hmul2bf(uint32_t a, uint32_t b) { uint32_t d; asm("mul.rn.bf16x2 %0, %1, %2;" : "=r"(d) : "r"(a), "r"(b)); return d; }

__device__ __forceinline__ uint32_t sq2bf(uint32_t a, uint32_t b) { const uint32_t d = hadd2bf(a, b); return hfma2bf(d, d, 0u); }

__host__ __device__ constexpr int b2_stage(int t) { return t < 48 ? t : t < 51 ? t - 1 : t - 2; }
__host__ __device__ constexpr bool early_wait(int t) { return t > 0 && (((EWMASK) >> t) & 1); }
template <int N, int MODE, int TC, int KK>
__device__ __forceinline__ void mma_k16(float (&acc)[N / 2], uint64_t da, uint64_t db, int sd) {
  constexpr uint32_t slot = SB0 + (TC < 0 ? 0 : (TC & 3) * SLOT);
  constexpr uint32_t aslot = (TC >= 10 && TC < 20) ? SB0 + ((19 - TC) & 3) * SLOT : slot;
  constexpr uint32_t wo = SB0 + (TC < 52 ? (((TC + 4) >> 1) & 3) * SLOT + 16384 : PH_OFF + 20480) + (TC & 1) * 10240;
  constexpr uint32_t oa = SB0 + (TC == 48 ? VH_OFF : TC == 51 ? 16384 : (b2_stage(TC) & 3) * SLOT);
  wgmma<N, 0, MODE != 1, MODE == 3 ? dlo(oa + KK * 4096, 2048) : MODE == 2 ? dlo(slot + KK * 4096, 2048) : dlo(aslot + KK * 32, 16),
        MODE == 1 ? dlo(slot + 16384 + KK * N * 32, N * 16) : MODE == 3 ? dlo(wo + KK * 2560, 1280) : dlo(slot + 16384 + KK * 2048, 8192)>(acc, da, db, sd);
}
template <int N, int MODE, int TC, bool RETIRE = true>
__device__ __forceinline__ void mma_step(float (&acc)[N / 2], uint32_t sb, int t, uint64_t da, uint64_t db, bool leader, uint32_t& nw, bool first = false, int half = -1) {
  if (TC < 0) { da += (uint32_t)((t & 3) * (SLOT / 16)); db += (uint32_t)((t & 3) * (SLOT / 16)); }
  if (half >= 0) { da += (uint32_t)(half * 512); db += (uint32_t)(half * 256); }
  const int st = MODE == 3 ? b2_stage(TC) : t;
  if (!early_wait(TC)) mbar_wait(sb + BAR_OFF + B_FULL + (st & 3) * 8, (st >> 2) & 1, nw);
  wg_fence();
  mma_k16<N, MODE, TC, 0>(acc, da, db, first ? 0 : 1);
  mma_k16<N, MODE, TC, 1>(acc, da, db, 1);
  if (half < 0) { mma_k16<N, MODE, TC, 2>(acc, da, db, 1); mma_k16<N, MODE, TC, 3>(acc, da, db, 1); }
  wg_commit();
  if (RETIRE) {
    wg_wait<1>();
    if (leader && t > 0 && TC < 49) mbar_arrive(sb + BAR_OFF + B_EMPTY + ((t - 1) & 3) * 8);
  }
  if (TC >= 0 && early_wait(TC + 1)) mbar_wait(sb + BAR_OFF + B_FULL + ((TC + 1) & 3) * 8, ((TC + 1) >> 2) & 1, nw);
}

template <int N> __device__ __forceinline__ void lds_cs(float (&c)[N], uint32_t a) {
#pragma unroll
  for (int i = 0; i < N / 4; i++) { const float4 v = lds128f(a + i * 16); c[4 * i] = v.x; c[4 * i + 1] = v.y; c[4 * i + 2] = v.z; c[4 * i + 3] = v.w; }
}
template <int NA>
__device__ __forceinline__ void fm_logits(const float (&acc)[NA], const float (&c)[20], float nm0, float nm1, float (&a)[20], float (&b)[20]) {
#pragma unroll
  for (int j = 0; j < 10; j++) {
    a[2 * j] = fmaf(c[2 * j], nm0, acc[4 * j]); a[2 * j + 1] = fmaf(c[2 * j + 1], nm0, acc[4 * j + 1]);
    b[2 * j] = fmaf(c[2 * j], nm1, acc[4 * j + 2]); b[2 * j + 1] = fmaf(c[2 * j + 1], nm1, acc[4 * j + 3]);
  }
}
__device__ __forceinline__ void fm_range(const float (&a)[20], float& mx, float& mn) {
  float m0 = fmaxf(a[0], a[1]), m1 = fmaxf(a[2], a[3]), n0 = fminf(a[0], a[1]), n1 = fminf(a[2], a[3]);
#pragma unroll
  for (int i = 4; i < 20; i += 2) { m0 = fmaxf(m0, a[i]); m1 = fmaxf(m1, a[i + 1]); n0 = fminf(n0, a[i]); n1 = fminf(n1, a[i + 1]); }
  mx = fmaxf(m0, m1); mn = fminf(n0, n1);
}
__device__ __forceinline__ void fm_args(const float (&a)[20], float mx, float mn, float sc, float (&ep)[20], float (&en)[20]) {
  const float op = -sc * mx, on = sc * mn;
#pragma unroll
  for (int i = 0; i < 20; i++) { ep[i] = fmaf(a[i], sc, op); en[i] = fmaf(a[i], -sc, on); }
}
template <int I0, int I1> __device__ __forceinline__ void fm_ex2(float (&e)[20]) {
#pragma unroll
  for (int i = I0; i < I1; i++) e[i] = ex2f(e[i]);
}
template <int I0 = 0>
__device__ __forceinline__ uint32_t fm_exp(float (&e)[20], uint32_t (&p)[10], float f) {
  fm_ex2<I0, 20>(e);
  float s0 = e[0] + e[1], s1 = e[2] + e[3];
#pragma unroll
  for (int i = 4; i < 20; i += 2) { s0 += e[i]; s1 += e[i + 1]; }
#pragma unroll
  for (int j = 0; j < 10; j++) p[j] = pack2(e[2 * j], e[2 * j + 1]);
  const float inv = f * rcpf(s0 + s1);
  return pack2(inv, inv);
}
__device__ __forceinline__ void fm_put(uint32_t (&p)[10], uint32_t ip, uint32_t (&n)[10], uint32_t in, uint32_t ps) {
#pragma unroll
  for (int j = 0; j < 10; j++) { p[j] = hfma2bf(p[j], ip, 0u); n[j] = hfma2bf(n[j], in, 0u); }
  sts128(ps, p[0], p[1], p[2], p[3]); sts128(ps + 2048, p[4], p[5], p[6], p[7]); sts128(ps + 4096, p[8], p[9], n[8], n[9]);
  sts128(ps + 6144, n[0], n[1], n[2], n[3]); sts128(ps + 8192, n[4], n[5], n[6], n[7]);
}

}

__global__ void __cluster_dims__(2, 1, 1) __launch_bounds__(NTHR, 1) fused_kernel(const __grid_constant__ Params p) {
  extern __shared__ __align__(1024) uint8_t smem_raw[];
  const uint32_t sb = smem_u32(smem_raw);
  const int tid = threadIdx.x;
  if ((sb & 0x3FFFF) != SB0) return;
  const int pos = p.tile[blockIdx.x >> 1] + (blockIdx.x & 1);
  const int r = pos >> 3, c = pos & 7, ks = c & 1;
#define BMAP 0
  const int rb = BMAP == 0 ? r : BMAP == 1 ? (r & ~1) + ((c >> 1) & 1) : (r & ~3) + (c >> 1);
  const int jb = BMAP == 0 ? c >> 1 : BMAP == 1 ? 2 * (r & 1) + (c >> 2) : r & 3;
  const int a0 = 5 * (jb >> 1) + 3 * (jb & 1);
  const int pg = 10 * (jb >> 1) + 4 + (jb & 1);
  const uint32_t bars = sb + BAR_OFF;

  const int warp = __shfl_sync(~0u, tid >> 5, 0), lane = tid & 31;
  if (warp == 8) {
    if (elect_one()) {
      prefetch_map(&p.mX); prefetch_map(&p.mW1);
#pragma unroll
      for (int s = 0; s < NSLOT; s++) mbar_init(bars + B_FULL + s * 8, 1);
      asm volatile("fence.mbarrier_init.release.cluster;" ::: "memory");
#pragma unroll 1
      for (int t = 0; t < NSLOT; t++) {
        mbar_expect(bars + B_FULL + t * 8, t == TF - 1 ? 40960 + 3200 : 40960);
        tma2d(sb + t * SLOT, &p.mX, t * 64, r * 128, bars + B_FULL + t * 8);
        tma3d(sb + t * SLOT + 16384, &p.mW1, t * 64, 3 * c, bars + B_FULL + t * 8);
        TR(2, t);
      }
    }
  } else if (warp == 9) {
    if (elect_one()) {
      prefetch_map(&p.mQs); prefetch_map(&p.mWts); prefetch_map(&p.mW1s);
#pragma unroll
      for (int s = 0; s < 17; s++) mbar_init(bars + B_EMPTY + s * 8, (s < 4 || s == 10) ? 2 : (s == 6 ? 8 : 1));
      asm volatile("fence.mbarrier_init.release.cluster;" ::: "memory");
    }
  } else if (warp == 10) {
    if (lane < 28) prefetch_l2(lane < 16 ? (const char*)p.x + (uint32_t)((pos * 16 + lane) * 1280) : (const char*)p.w1 + (uint32_t)((pos >> 1) * 3456 + ((pos & 1) * 12 + lane - 16) * 128));
  }
  __syncthreads();
  asm volatile("barrier.cluster.arrive.relaxed.aligned;" ::: "memory");
  if (warp == 0 && elect_one()) {
    if (SDLY) asm volatile("nanosleep.u32 %0;" ::"n"(SDLY));
    tma1d(sb + SL_PHI, p.wphi + c * 1600, 3200, bars + B_FULL + (TF - 1) * 8);
    mbar_expect(bars + B_SLAB, 19200 + 1920);
    tma3d0(sb + SL_QKV, &p.mQs, c * 80, r * 40, bars + B_SLAB);
    tma2d(sb + SL_WT, &p.mWts, 1536 + c * 24, r * 40, bars + B_SLAB);
  }

  if (tid >= 256) {
    asm volatile("setmaxnreg.dec.sync.aligned.u32 56;");
    if ((warp | 2) == 11) {
      mbar_wait_long(bars + B_SLAB2, 0);
      if (warp == 11) {
        const uint32_t pp = pos >> 1, co = (lane >> 2) * 81920 + (pos & 1) * 640 + 320 + (lane & 3) * 16;
        const char* sp = (const char*)p.w2 + (co + ((pp & 14) * 4 + (pp >> 4) * 2 + (pp & 1)) * 1280);
        uint8_t* d = g_s.wx + (((pos & 1) * 27 + (lane >> 2)) * 8192 + pp * 128 + (((lane & 3) ^ (pp & 7)) << 4));
        if (lane == 0) TR(3, 19);
        uint4 v[4];
        v[0] = ldg128(sp); v[1] = ldg128(sp + 8 * 81920); v[2] = ldg128(sp + 16 * 81920);
        if (lane < 12) v[3] = ldg128((const char*)p.w2 + (co + pp * 1280 + 24 * 81920));
#pragma unroll
        for (int k = 0; k < 4; k++) if (k < 3 || lane < 12) stg128(d + k * 65536, v[k].x, v[k].y, v[k].z, v[k].w);
      }
#pragma unroll 1
      for (int i = (warp - 9) >> 1; i < 7; i += 2) {
        const bool colev = ((0xB >> i) & 1) && lane == 0;
        asm volatile("bar.sync %0, %1;" ::"r"(NB_PUB + i), "r"(i == 3 ? 320 : 288) : "memory");
        if (lane < (i == 1 ? 2 : 1)) {
          asm volatile("fence.proxy.async;" ::: "memory");
          asm volatile("red.relaxed.gpu.global.add.u32 [%0], %1;" ::"l"(g_s.flags + (uint32_t)((colev ? 16 + c : r) * 32 + i)), "r"(colev ? 1 : 2) : "memory");
        }
        if (lane == 0 && i < 6) TR(3, 2 * i + 1);
        if (i == 0) {
          float4* zn = reinterpret_cast<float4*>(g_s.z[~lds32(bars + B_EPOCH) & 1]) + (uint32_t)(pos * 80 + lane);
          zn[0] = zn[32] = make_float4(0.f, 0.f, 0.f, 0.f);
          if (lane < 16) zn[64] = make_float4(0.f, 0.f, 0.f, 0.f);
        }
        if (i == 1) {
          mbar_wait_long(bars + B_CS, 0);
          if (lane == 0) TR(3, 12);
#pragma unroll 1
          for (uint32_t j = lane; j < 288; j += 32) {
            const float x = __uint_as_float(lds32(j < 128 ? sb + SL_ST + j * 8 + 4 : sb + CS_OFF + ((j >> 1) & 3) * CS_QS + ((j + 64) >> 3) * 8 + (j & 1) * 4));
            const float y = j < 128 ? 0.5f * x : x;
            const uint32_t hh = pack2(y, y), ll = pack2(y - bf_lo(hh), y - bf_lo(hh));
            sts128(sb + EX_A + j * 16, j < 128 ? (hh & 0xffffu) | (ll << 16) : hh, (j < 128 ? hh : ll) & 0xffffu, 0u, 0u);
          }
          fence_async_smem();
          __syncwarp();
          if (lane == 0) mbar_arrive(bars + B_DEP + 24);
        }
        if (i == 2) {
          const char* src = (const char*)p.wo + (uint32_t)((r * 40 + (lane & 7)) * 1280 + (lane >> 3) * 16);
          uint8_t* d = g_s.wo + (uint32_t)((c * 80 + (r & 1) * 40 + (r >> 1) * 5) * 1280 + lane * 16);
#pragma unroll 1
          for (int h = 0; h < 3; h++) {
            const char* sh = src + (h < 2 ? (a0 + ks) * 128 + h * 64 : pg * 64 + ks * 32);
            uint4 v[5];
#pragma unroll
            for (int k = 0; k < 5; k++) v[k] = ldg128(sh + k * 10240);
            if (h < 2 || lane < 16) {
#pragma unroll
              for (int k = 0; k < 5; k++) stg128(d + k * 1280, v[k].x, v[k].y, v[k].z, v[k].w);
            }
            d += 512;
          }
          nb_arrive<NB_PUB + 3, 320>();
        }
      }
    } else if (warp == 10) {
      if (elect_one()) {
        const unsigned epoch = ld_rlx(g_s.flags + FL_EPOCH * 32);
        sts32(bars + B_EPOCH, epoch); mbar_arrive(bars + B_SLAB2);
        const float* z = g_s.z[epoch & 1];
        mbar_expect(bars + B_CS, CS_N * 4 + 1024); mbar_expect(bars + B_KVB, 18432);
#pragma unroll 1
        for (int i = 0; i < 8; i++) {
          const int ev = i - (i > 1);
          flag_wait(g_s.flags + (uint32_t)((((0x13 >> i) & 1) ? 16 + c : r) * 32 + ev), epoch * 16 + 16);
          fence_async_glob();
          if (i == 1) tma1d(sb + CS_OFF, z + (KV_FLOATS + c * CS_N), CS_N * 4, bars + B_CS);
          if (i == 2) { tma1d(sb + SL_ST, g_s.stats + r * 128, 1024, bars + B_CS); TR(3, 18); }
          else if (i == 4) { TR(3, 13); tma1d(sb + VH_OFF, z + c * 4608, 18432, bars + B_KVB); }
          else mbar_arrive(bars + B_DEP + (i == 7 ? 0 : ev * 8));
        }
      }
    } else {
      if (elect_one()) {
        int t = NSLOT;
#define ACQ(bytes) const uint32_t slot = sb + (t & 3) * SLOT, fb = bars + B_FULL + (t & 3) * 8; \
                   mbar_wait_long(fb + B_EMPTY, ((t >> 2) & 1) ^ 1); mbar_expect(fb, bytes); if (t < 49) TR(2, t);
        mbar_expect(bars + B_XG, 20480); mbar_expect(bars + B_XS, 3 * 20480 + 16384);
#pragma unroll 1
        for (; t < 30; t++) {
          const int k = t < 10 ? t : (t < 20 ? 19 - t : t - 20);
          const bool ldx = (XMASK >> t) & 1;
          ACQ((ldx ? 16384 : 0) + (t < 10 ? 24576 : (t < 20 ? 20480 : 13312)))
          if (ldx) tma2d(sb + (k & 3) * SLOT, &p.mX, k * 64, r * 128, fb);
          if (t == 10) { mbar_wait_long(bars + B_DEP, 0); fence_async_glob(); TR(2, 49); }
          tma3d(slot + 16384, t < 10 ? &p.mW1 : (t < 20 ? &p.mWp2 : &p.mWp3), t < 10 ? k * 64 : (t < 20 ? 0 : 20), t < 10 ? 3 * c : c * 80 + k * 8, fb);
          if (t == 4) { mbar_expect(bars + B_SLAB2, 15360); tma3d(sb + SL_W1, &p.mW1s, r * 40, 3 * c, bars + B_SLAB2); }
          if (t >= 5 && t < 10) prefetch_map(&p.mWp2 + (t - 5));
          if (t >= 10 && t < 20) {
            asm volatile("cp.async.bulk.prefetch.L2.global [%0], 1728;" ::"l"((const char*)p.w2 + (uint32_t)((pos * 10 + k) * 1728)) : "memory");
            asm volatile("cp.async.bulk.prefetch.L2.global [%0], 640;" ::"l"((const char*)p.wo + (uint32_t)((pos * 10 + k) * 640)) : "memory");
          }
        }
        mbar_wait_long(bars + B_DEP + 16, 0); fence_async_glob(); TR(2, 50);
#pragma unroll 1
        for (; t < 44; t++) {
          const int kg = t < 42 ? (12 * ks + t - 30) * 8 : (t == 42 ? 192 + 16 * ks : 200 + 4 * ks), sh = t == 43;
          const CUtensorMap* m = &p.mW2a + max(t - 41, 0);
          ACQ(40960 >> sh)
          tma5d(slot + 16384, m, kg, a0 + ks, fb);
          tma5d(slot + 24576, m, kg, a0 + 1 - ks, fb);
          if (jb & 1) tma1d(slot + 32768, g_s.wx + ((jb >> 1) * 216 + kg) * 1024, 8192 >> sh, fb);
          else tma5d(slot + 32768, m, kg, a0 + 2, fb);
          if (t == 42) { mbar_wait_long(bars + B_DEP + 32, 0); fence_async_glob(); TR(2, 51); }
          tma1d(slot, g_s.ho + (rb * 296 + kg) * 2048, 16384 >> sh, fb);
        }
        const uint8_t* so = g_s.ho + (rb * 37 + 27) * 16384;
        const uint8_t* sw = g_s.wo + c * 102400;
#pragma unroll 1
        for (; t < 52; t++) {
          ACQ(t < 46 ? 16384 + 20480 : (t == 49 ? 32768 : 16384))
          if (t < 46) tma1d(slot + 16384, sw, 20480, fb);
          if (t == 44) { tma1d(sb + PH_OFF + 20480, sw + 81920, 20480, bars + B_XS); if (!OW44) { sw += 20480; continue; } }
          if (t == 45 - OW44 || t == 48) { mbar_wait_long(bars + B_DEP + (t == 48 ? 0 : 40), t == 48); fence_async_glob(); if (t < 48) TR(2, 52); }
          if (!OW44 && t == 45) { tma1d(sb, so, 16384, bars + B_FULL); so += 16384; }
          tma1d(slot, so, 16384, fb); so += 16384;
          if (t == 45) tma1d(sb + VH_OFF, so + 32768, 16384, bars + B_XS);
          if (t == 46 || t == 47) tma1d(slot + 16384, sw, 20480, bars + B_XS);
          if (t == 49) tma1d(sb + 16384, so, 16384, fb);
          if (t == 47 || t == 49) so += 16384;
          sw += 20480;
        }
#undef ACQ
      }

    }
  } else {
    asm volatile("setmaxnreg.inc.sync.aligned.u32 224;");
    const int wg = warp >> 2, W = warp, g = lane >> 2, q = lane & 3;
    const bool leader = (tid & 127) == 0;
    uint32_t nw = 0;
    const uint64_t woA = (uint32_t)(wg * 512), woN = (uint32_t)(wg * 64);
#define DA(MODE, I) (MODE >= 2 ? p.dns[I] + woN : p.dsw[I] + woA)
#define DB(MODE, I) ((MODE & 1) ? p.dns[I] : p.dsw[I])
#define STEP(N, MODE, ACC, T, ...) mma_step<N, MODE, T>(ACC, sb, T, DA(MODE, (T) >> 2), DB(MODE, (T) >> 2), leader, nw, ##__VA_ARGS__); TRC(T);
#define ISSUE(N, MODE, ACC, T) mma_step<N, MODE, T, false>(ACC, sb, T, DA(MODE, (T) >> 2), DB(MODE, (T) >> 2), leader, nw);
#define RETIRE(T) wg_wait<1>(); if (leader) mbar_arrive(bars + B_EMPTY + (((T) - 1) & 3) * 8); TRC(T);
#define STEPR(N, MODE, ACC, T, ...) mma_step<N, MODE, -1>(ACC, sb, T, DA(MODE, 14), DB(MODE, 14), leader, nw, ##__VA_ARGS__); TRC(T);

    const bool on = p.one != 0;
    float acc1[96];
    {
      const uint32_t ones = 0x3f803f80u, l7 = lane & 7, fh = W & 3;
      const uint32_t srow = pos * 16 + W * 2 + (lane >> 4);
      uint32_t wl = sb + SL_PHI + fh * 800 + 4 * q + (4 * (g >> 1) + (g & 1)) * 40, wh = sb + SL_PHI + fh * 800 + 4 * q + (g & 3) * 40 + 640;
      uint32_t ws = sb + SL_QKV + (wg ? 0 : 6400) + g * 160 + fh * 40 + 8 * q, w8 = sb + SL_QKV + (wg ? 0 : 6400) + g * 160 + fh * 40 + 4 * (q & 1) + 32;
      uint32_t n = wg * 160 + 8 * (g >> 1) + 2 * fh + (g & 1);
      const char* xp = (const char*)p.x + (srow * (2u * D_) + (lane & 15) * 16u);
      auto vrow = [&](int col) {
        const int h = (col * 205) >> 12;
        int d = col - h * 20 - 4 * (h & 1);
        if (d < 0) d += 20;
        const int f = d < 16 ? (d & 8) + 4 * (d & 1) + ((d & 7) >> 1) : 16 + 2 * (d & 1) + ((d >> 1) & 1);
        return 80 + 8 * (f >> 1) + 2 * h + (f & 1);
      };
      uint32_t r0 = vrow(W * 8 + g), r1 = W < 2 ? vrow(64 + W * 8 + g) : 224 + W * 8 + g;
      uint32_t va = sb + SL_QKV + 12800 + W * 16, vb = W < 2 ? va + 128 : sb + SL_WT + min(W - 2, 2) * 16;
      const uint32_t pb = W < 2 ? 160 : 48;
      uint32_t vc = (lane & 8) ? vb + (32 + l7) * pb : va + (32 + l7) * 160;
      va += lane * 160; vb += lane * pb;
      auto csi = [](uint32_t x) { return ((x >> 1) & 3) * (CS_QS / 4) + (x >> 3) * 2 + (x & 1); };
      uint32_t ci0 = csi(192 + (q < 3 ? n + 32 * q : r0)), ci1 = csi(q < 3 ? W * 24 + 8 * q + g : 192 + r1);
      asm volatile("" : "+r"(ci0), "+r"(ci1), "+r"(wl), "+r"(wh), "+r"(ws), "+r"(w8), "+r"(n), "+l"(xp), "+r"(r0), "+r"(r1), "+r"(va), "+r"(vb), "+r"(vc));
#pragma unroll 1
      for (int t = 0; t < TF; t++) { STEPR(192, 0, acc1, t, t == 0) }
      uint32_t fa[12];
      fa[0] = lds32(wl); fa[1] = lds32(wl + 16); fa[2] = lds32(wl + 80); fa[3] = lds32(wl + 96);
      fa[4] = lds32(wh); fa[5] = lds32(wh + 16); fa[6] = lds32(wl + 32); fa[7] = lds32(wl + 112); fa[8] = lds32(wh + 32);
#pragma unroll
      for (int i = 0; i < 9; i++) fa[i] = movtrans(fa[i]);
      if (q >= 2) { fa[4] = 0; fa[5] = 0; fa[8] = 0; }
      fa[9] = wl; fa[10] = wh; fa[11] = ws;
      pinu(fa);
      uint4 xs[5];
      if (on) {
#pragma unroll
        for (int i = 0; i < 5; i++) xs[i] = ldg128(xp + 256 * i);
      }
      STEP(192, 0, acc1, TF + 0)
      mbar_wait(bars + B_SLAB, 0, nw);
      if (tid == 0) TR(3, 20);
      uint8_t* const wpc = g_s.wp + (uint32_t)((c * 80 + r * 5) * WP_KG + q * 4);
      auto put5 = [&](uint32_t row, uint32_t a, uint32_t b, uint32_t cc, uint32_t d, uint32_t e) {
        uint8_t* dst = wpc + row * 16;
        stg32(dst, a); stg32(dst + WP_KG, b); stg32(dst + 2 * WP_KG, cc); stg32(dst + 3 * WP_KG, d); stg32(dst + 4 * WP_KG, e);
      };
      const uint4 t0 = ldsm4t(va), t1 = ldsm4t(vb), t2 = ldsm4t(vc);
      uint32_t k0[16];
      uint2 fb[5]; uint32_t fb8[5];
#pragma unroll
      for (int nt = 0; nt < 5; nt++) { fb[nt] = lds64(ws + nt * 1280); fb8[nt] = lds32(w8 + nt * 1280); }
      if (on) put5(r0, t0.x, t0.y, t0.z, t0.w, t2.x);
      if (W < 5) put5(r1, t1.x, t1.y, t1.z, t1.w, t2.y);
      auto fold = [&]() {
#pragma unroll
        for (int nt = 0; nt < 5; nt++) {
          float e0[4], e1[4];
          mma16816(e0, fa[0], fa[1], fa[2], fa[3], fb[nt].x, fb[nt].y);
          mma1688(e0, fa[4], fa[5], fb8[nt]);
          mma16816(e1, fa[6], fa[9], fa[7], fa[10], fb[nt].x, fb[nt].y);
          mma1688(e1, fa[8], fa[11], fb8[nt]);
          k0[2 * nt] = pack2(e0[0], e0[1]); k0[2 * nt + 1] = pack2(e0[2], e0[3]); k0[nt < 4 ? 12 + nt : 10] = pack2(e1[0], e1[1]);
        }
        k0[11] = fa[11];
      };
      auto putk = [&]() {
        put5(n, k0[0], k0[2], k0[4], k0[6], k0[8]); put5(n + 32, k0[1], k0[3], k0[5], k0[7], k0[9]);
        if (g < 4) put5(n + 64, k0[12], k0[13], k0[14], k0[15], k0[10]);
        nb_arrive<NB_PUB, 288>();
      };
      if (!MRG) fold();
      STEP(192, 0, acc1, TF + 1)
      if (!MRG) { putk(); STEP(192, 0, acc1, TF + 2) }
      mbar_wait(bars + B_SLAB2, 0, nw);
      auto swz = [&](uint32_t C) { return (C >> 3) * 5120 + (((C & 7) ^ l7) << 4); };
      const uint32_t wa = sb + SL_W1;
      const uint4 c0 = ldsm4t(wa + lane * 128 + swz(3 * W)), c1 = ldsm4t(wa + lane * 128 + swz(3 * W + 1)), c2 = ldsm4t(wa + lane * 128 + swz(3 * W + 2));
      const uint4 c3 = ldsm4t(wa + (32 + l7) * 128 + swz(3 * W + min(lane >> 3, 2)));
      const uint32_t x0 = __shfl_sync(~0u, xs[0].x, 0, 16) << 16;
      const uint32_t pv = ((x0 >> 16) | x0) ^ 0x80008000u;
      float s[4] = {0.f, 0.f, 0.f, 0.f}, u[4] = {0.f, 0.f, 0.f, 0.f};
      float u0[4], u1[4], u2[4], e1[4] = {0.f, 0.f, 0.f, 0.f}, e2[4] = {0.f, 0.f, 0.f, 0.f}, e3[4] = {0.f, 0.f, 0.f, 0.f}, e4[4] = {0.f, 0.f, 0.f, 0.f}, p0[4], p1[4], p2[4], p3[4];
      uint4 ys[5];
#pragma unroll
      for (int i = 0; i < 5; i++) { ys[i].x = sq2bf(xs[i].x, pv); ys[i].y = sq2bf(xs[i].y, pv); ys[i].z = sq2bf(xs[i].z, pv); ys[i].w = sq2bf(xs[i].w, pv); }
      if (on) {
#pragma unroll
        for (int i = 0; i < 5; i++) {
          mma16816a(s, xs[i].x, xs[i].y, xs[i].z, xs[i].w, ones, ones);
          mma16816a(u, ys[i].x, ys[i].y, ys[i].z, ys[i].w, ones, ones);
        }
        mma16816(u0, c0.x, c0.y, c0.z, c0.w, ones, ones); mma16816(u1, c1.x, c1.y, c1.z, c1.w, ones, ones); mma16816(u2, c2.x, c2.y, c2.z, c2.w, ones, ones);
        mma1688(e1, c3.x, c3.y, ones); mma1688(e2, c3.z, c3.w, ones);
        if (MRG) fold();
        mma1688(e4, k0[10], k0[11], ones);
        mma16816(p0, k0[0], k0[1], k0[2], k0[3], ones, ones); mma16816(p1, k0[12], k0[13], k0[14], k0[15], ones, ones);
        mma16816a(p0, k0[4], k0[5], k0[6], k0[7], ones, ones); mma1688(p0, k0[8], k0[9], ones);
        mma16816(p2, t0.x, t0.y, t0.z, t0.w, ones, ones); mma16816(p3, t1.x, t1.y, t1.z, t1.w, ones, ones); mma1688(e3, t2.x, t2.y, ones);
      }
      STEP(192, 0, acc1, TF + 3 - MRG)
      if (MRG) putk();
      if (on) {
        float* zcs = g_s.z[lds32(bars + B_EPOCH) & 1] + (KV_FLOATS + c * CS_N);
        if (q != 2 || g < 4) red1(zcs + ci0, q == 0 ? p0[0] : q == 1 ? p0[2] : q == 2 ? p1[0] + p1[2] + e4[0] : p2[0] + p2[2] + e3[0]);
        if (q < 3 || W < 5)
          red1(zcs + ci1, q == 0 ? u0[0] + u0[2] + e1[0] : q == 1 ? u1[0] + u1[2] + e1[2] : q == 2 ? u2[0] + u2[2] + e2[0] : p3[0] + p3[2] + e3[2]);
        float m = s[0] + s[2], v = u[0] + u[2];
        m += __shfl_xor_sync(~0u, m, 4); v += __shfl_xor_sync(~0u, v, 4);
        m += __shfl_xor_sync(~0u, m, 8); v += __shfl_xor_sync(~0u, v, 8);
        const float nmean = m * (-1.f / D_);
        m = __uint_as_float(x0) + nmean;
        float rstd;
        asm("rsqrt.approx.ftz.f32 %0, %1;" : "=f"(rstd) : "f"(fmaxf(fmaf(v, 1.f / D_, -m * m), 0.f) + 1e-5f));
        if ((lane & 15) == 0) stg64(&g_s.stats[srow], __float_as_uint(rstd), __float_as_uint(nmean));
      }
      nb_arrive<NB_PUB + 1, 288>();
#pragma unroll 1
      for (int t = TF + 4 - MRG; t < 10; t++) { STEPR(192, 0, acc1, t) }
    }

    float acc2[80];
    STEP(160, 1, acc2, 10, true)
    pin(acc1);
    if (HSM == 3) { STEP(160, 1, acc2, 11) }
    mbar_wait(bars + B_CS, 0, nw);
    float2 st0, st1;
    { const uint2 a = lds64(sb + SL_ST + (W * 16 + g) * 8), b = lds64(sb + SL_ST + (W * 16 + g) * 8 + 64);
      st0 = make_float2(__uint_as_float(a.x), __uint_as_float(a.y)); st1 = make_float2(__uint_as_float(b.x), __uint_as_float(b.y)); }
    const uint32_t csq = sb + CS_OFF + q * CS_QS;
    uint8_t* const hth = g_s.ho + (uint32_t)(r * 37 * 16384 + W * 256 + g * 16);
    {
      float cc[2][8];
      lds_cs(cc[0], csq); lds_cs(cc[1], csq + 32);
      uint8_t* d = hth + (uint32_t)((c * 24 + 2 * q) * 2048);
      keep(d);
      float h0 = 0.f, h1 = 0.f;
      uint32_t u[4];
      auto part = [&](auto UC, auto J0, auto J1) {
        constexpr int i = decltype(UC)::value >> 1, R = decltype(UC)::value & 1;
        const float hs = R ? h1 : h0, nm = R ? st1.y : st0.y;
#pragma unroll
        for (int jj = decltype(J0)::value; jj < decltype(J1)::value; jj++)
          u[jj] = pack2(silu_half(hs * fmaf(cc[i & 1][2 * jj], nm, acc1[16 * i + 4 * jj + 2 * R])), silu_half(hs * fmaf(cc[i & 1][2 * jj + 1], nm, acc1[16 * i + 4 * jj + 2 * R + 1])));
        if (decltype(J1)::value == 4) {
          if (R && i < 4) lds_cs(cc[i & 1], csq + (i + 2) * 32);
          stg128(d + ((i >> 1) * 8 + (i & 1)) * 2048 + R * 128, u[0], u[1], u[2], u[3]);
        } else pinu(u);
      };
      auto ext = [&]() {
        mbar_wait(bars + B_DEP + 24, 0, nw);
        wg_fence();
        wgmma<160, 0, 0, dlo(SB0 + EX_A, 0), dlo(SB0 + EX_B, 0)>(acc2, DA(2, 14), DB(1, 14), 1);
      };
      auto twice = [&](auto KC) {
        constexpr int k = decltype(KC)::value;
        STEP(160, 1, acc2, 9 + HSM + 2 * k)
        if (k == 0) { h0 = 0.5f * st0.x; h1 = 0.5f * st1.x; keep(h0, h1); }
        if (on) { part(IC<3 * k>(), IC<0>(), IC<4>()); part(IC<3 * k + 1>(), IC<0>(), IC<2>()); }
        if (k == 3) ext();
        STEP(160, 1, acc2, 10 + HSM + 2 * k)
        if (on) { part(IC<3 * k + 1>(), IC<2>(), IC<4>()); part(IC<3 * k + 2>(), IC<0>(), IC<4>()); }
      };
      auto triple = [&](auto KC) {
        constexpr int k = decltype(KC)::value;
        STEP(160, 1, acc2, 11 + 3 * k)
        if (k == 0) { h0 = 0.5f * st0.x; h1 = 0.5f * st1.x; keep(h0, h1); }
        if (on) { part(IC<4 * k>(), IC<0>(), IC<4>()); part(IC<4 * k + 1>(), IC<0>(), IC<2>()); }
        STEP(160, 1, acc2, 12 + 3 * k)
        if (on) { part(IC<4 * k + 1>(), IC<2>(), IC<4>()); part(IC<4 * k + 2>(), IC<0>(), IC<3>()); }
        if (k == 2) ext();
        STEP(160, 1, acc2, 13 + 3 * k)
        if (on) { part(IC<4 * k + 2>(), IC<3>(), IC<4>()); part(IC<4 * k + 3>(), IC<0>(), IC<4>()); }
      };
      if (HSM >= 2) {
        twice(IC<0>()); twice(IC<1>()); twice(IC<2>()); twice(IC<3>());
        nb_arrive<NB_PUB + 2, 288>();
        if (HSM == 2) { STEP(160, 1, acc2, 19) }
      } else {
        triple(IC<0>()); triple(IC<1>()); triple(IC<2>());
        nb_arrive<NB_PUB + 2, 288>();
      }
    }

    constexpr float LOG2E = 1.4426950408889634f;
    const uint32_t phs = sb + PH_OFF + q * PH_HS + W * 256 + g * 16;
    float acc3[52], accg[80];
    {
      float a[20], b[20];
      {
        STEP(104, 1, acc3, 20, true)
        pin(acc2);
#pragma unroll
        for (int j = 0; j < 20; j++) { a[j] = acc2[4 * (j >> 1) + (j & 1)]; b[j] = acc2[4 * (j >> 1) + 2 + (j & 1)]; }
      }
      uint32_t u[12], w[12];
      {
        const uint32_t z0 = pack2(rcpf(st0.x), 0.f), z1 = pack2(rcpf(st1.x), 0.f);
        const bool odd = q & 1;
#pragma unroll
        for (int j = 0; j < 10; j++) {
          u[j] = pack2(acc2[40 + 4 * j], acc2[41 + 4 * j]);
          w[j] = pack2(acc2[42 + 4 * j], acc2[43 + 4 * j]);
        }
        u[10] = odd ? 0u : u[9]; u[11] = odd ? u[9] : 0u; u[9] = odd ? u[8] : z0; u[8] = odd ? z0 : u[8];
        w[10] = odd ? 0u : w[9]; w[11] = odd ? w[9] : 0u; w[9] = odd ? w[8] : z1; w[8] = odd ? z1 : w[8];
      }
      {
        {
          const uint32_t vhs = sb + VH_OFF + q * VH_HS + W * 256 + g * 16;
          float f = st0.x;
          pinu(u); pinu(w);
#pragma unroll 1
          for (int rr = 0; rr < 2; rr++) {
            float ep[20], en[20], mx, mn; uint32_t pp[10], pn[10], ip, in;
            fm_range(a, mx, mn); keep(mx, mn);
            STEPR(104, 1, acc3, 21 + 4 * rr)
            if (on) {
              fm_args(a, mx, mn, f * LOG2E, ep, en);
              fm_ex2<0, XA>(ep);
              pin(ep); pin(en);
            }
            STEPR(104, 1, acc3, 22 + 4 * rr)
            if (on) {
              ip = fm_exp<XA>(ep, pp, f); fm_ex2<0, XB>(en); pinu(pp); pin(en);
              sts128(vhs + rr * 128, u[0], u[1], u[2], u[3]); sts128(vhs + rr * 128 + 2048, u[4], u[5], u[6], u[7]); sts128(vhs + rr * 128 + 4096, u[8], u[9], u[10], u[11]);
            }
            STEPR(104, 1, acc3, 23 + 4 * rr)
            if (on) {
              in = fm_exp<XB>(en, pn, f);
              fm_put(pp, ip, pn, in, phs + rr * 128);
            }
            if (rr == 0) {
              STEP(104, 1, acc3, 24)
#pragma unroll
              for (int j = 0; j < 20; j++) asm volatile("mov.b32 %0, %1;" : "=f"(a[j]) : "f"(b[j]));
#pragma unroll
              for (int j = 0; j < 12; j++) asm volatile("mov.b32 %0, %1;" : "=r"(u[j]) : "r"(w[j]));
              f = st1.x;
            }
          }
          fence_async_smem();
        }
        float kv0[12], kv1[12];
        nb_sync<NB_ALL, 256>();
        wg_fence();
#pragma unroll 1
        for (int s = 0; s < 8; s++) {
          const uint64_t da = dhi(2048, 0) + (uint32_t)(wg * (2 * PH_HS / 16) + s * 16), db = dhi(2048, 0) + (uint32_t)(wg * (2 * VH_HS / 16) + s * 16);
          wgmma<24, 1, 1, dlo(SB0 + PH_OFF, 128), dlo(SB0 + VH_OFF, 128)>(kv0, da, db, s);
          wgmma<24, 1, 1, dlo(SB0 + PH_OFF + PH_HS, 128), dlo(SB0 + VH_OFF + VH_HS, 128)>(kv1, da, db, s);
        }
        wg_commit();
        const int w4 = W & 3;
        float* ke = g_s.z[lds32(bars + B_EPOCH) & 1] + (uint32_t)((4 * c + 2 * wg) * 1152 + (q >> 1) * 192 + (w4 * 16 + g) * 4 + 2 * (q & 1));
        keep(ke);
        auto redA = [&]() { if (w4 < 3) { red2(ke, kv0[0], kv0[1]); red2(ke + 384, kv0[4], kv0[5]); red2(ke + 768, kv0[8], kv0[9]); } };
        auto redB = [&]() { if (w4 < 3) { red2(ke + 1152, kv1[0], kv1[1]); red2(ke + 1536, kv1[4], kv1[5]); red2(ke + 1920, kv1[8], kv1[9]); } };
        auto redC = [&]() {
          if (w4 < 2) {
#pragma unroll
            for (int j = 0; j < 3; j++) { red2(ke + 32 + 384 * j, kv0[4 * j + 2], kv0[4 * j + 3]); red2(ke + 1184 + 384 * j, kv1[4 * j + 2], kv1[4 * j + 3]); }
          }
          nb_arrive<NB_PUB + 3, 320>();
        };
        float cc[20], ct[8];
        STEP(104, 1, acc3, 28)
        pin(kv0); pin(kv1);
        redA();
        STEP(104, 1, acc3, 29)
        lds_cs(cc, csq + 44 * 8);
        lds_cs(ct, csq + 54 * 8);
        redB();
        wg_wait<0>();
        if (leader) mbar_arrive(bars + B_EMPTY + 8);
        pin(acc3);
        float a2[20], b2[20], y[12];
        fm_logits(acc3, cc, st0.y, st1.y, a2, b2);
#pragma unroll
        for (int i = 0; i < 12; i++) y[i] = fmaf(ct[2 * (i >> 2) + (i & 1)], (i & 2) ? st1.y : st0.y, acc3[40 + i]);
        pin(a2); pin(b2); pin(y);
        mma_step<160, 2, 30, false>(accg, sb, 30, DA(2, 7), DB(2, 7), leader, nw, true); TRC(30);
        redC();
        nb_sync<NB_ALL, 256>();
        STEP(160, 2, accg, 31)
        {
          float sc = st0.x * LOG2E;
#pragma unroll 1
          for (int rr = 0; rr < 2; rr++) {
            float ep[20], en[20], mx, mn; uint32_t pp[10], pn[10], ip, in;
            fm_range(a2, mx, mn);
            fm_args(a2, mx, mn, sc, ep, en);
            if (rr == 0) {
#pragma unroll
              for (int j = 0; j < 20; j++) asm volatile("mov.b32 %0, %1;" : "=f"(a2[j]) : "f"(b2[j]));
            }
            pin(ep); pin(en); pin(a2);
            sc = st1.x * LOG2E;
            STEPR(160, 2, accg, 32 + 2 * rr)
            if (on) { ip = fm_exp(ep, pp, 1.f); pinu(pp); }
            STEPR(160, 2, accg, 33 + 2 * rr)
            if (on) { in = fm_exp(en, pn, 1.f); fm_put(pp, ip, pn, in, phs + rr * 128); }
          }
          fence_async_smem();
          const float h0 = 0.5f * st0.x, h1 = 0.5f * st1.x;
          uint8_t* d = hth + (uint32_t)((192 + 3 * c) * 2048 + q * 4);
#pragma unroll
          for (int jj = 0; jj < 3; jj++) {
            stg32(d + jj * 2048, pack2(silu_half(h0 * y[4 * jj]), silu_half(h0 * y[4 * jj + 1])));
            stg32(d + jj * 2048 + 128, pack2(silu_half(h1 * y[4 * jj + 2]), silu_half(h1 * y[4 * jj + 3])));
          }
        }
        nb_arrive<NB_PUB + 4, 288>();
      }
    }
    uint32_t peer;
    asm volatile("mapa.shared::cluster.u32 %0, %1, %2;" : "=r"(peer) : "r"(sb), "r"(ks ^ 1));
    {
      if (T_O > 37) { STEP(160, 2, accg, T_O - 2) }
      if (T_O > 36) { STEP(160, 2, accg, T_O - 1) }
      if (wg) nb_sync<NB_WG0 + 1, 128>(); else nb_sync<NB_WG0, 128>();
      asm volatile("barrier.cluster.wait.aligned;" ::: "memory");
      float o0[24], o1[24], o2[24], o3[24];
      mbar_wait(bars + B_KVB, 0, nw);
      if (tid == 0) TR(3, 14);
      wg_fence();
#pragma unroll 1
      for (int s = 0; s < 3; s++) {
        const uint64_t da = DA(2, 14) + (uint32_t)(s * 256 + (s < 2 ? dlo(0, 2048) : 0)), db = dhi(768, 0) + (uint32_t)(s * 16);
        wgmma<48, 0, 1, dlo(SB0 + PH_OFF, 0), dlo(SB0 + VH_OFF, 128)>(o0, da, db, s);
        wgmma<48, 0, 1, dlo(SB0 + PH_OFF + PH_HS, 0), dlo(SB0 + VH_OFF + 1 * 4608, 128)>(o1, da, db, s);
        wgmma<48, 0, 1, dlo(SB0 + PH_OFF + 2 * PH_HS, 0), dlo(SB0 + VH_OFF + 2 * 4608, 128)>(o2, da, db, s);
        wgmma<48, 0, 1, dlo(SB0 + PH_OFF + 3 * PH_HS, 0), dlo(SB0 + VH_OFF + 3 * 4608, 128)>(o3, da, db, s);
      }
      wg_commit();
      STEP(160, 2, accg, T_O)
      pin(o0); pin(o1); pin(o2); pin(o3);
      if (lane == 0) mbar_arrive_remote(peer + BAR_OFF + B_XRDY);
      auto onorm = [&](const float (&e)[24], const float (&o)[24], uint32_t (&u)[10]) {
        const float e0 = rcpf(__shfl_sync(~0u, e[17], 2, 4) + 1e-6f), e1 = rcpf(__shfl_sync(~0u, e[19], 2, 4) + 1e-6f);
        const float f0 = rcpf(__shfl_sync(~0u, o[17], 0, 4) + 1e-6f), f1 = rcpf(__shfl_sync(~0u, o[19], 0, 4) + 1e-6f);
        u[0] = pack2(e[1] * e0, e[5] * e0); u[1] = pack2(e[3] * e1, e[7] * e1); u[2] = pack2(e[9] * e0, e[13] * e0); u[3] = pack2(e[11] * e1, e[15] * e1);
        u[4] = q < 2 ? pack2(e[17] * e0, e[21] * e0) : pack2(o[17] * f0, o[21] * f0);
        u[5] = q < 2 ? pack2(e[19] * e1, e[23] * e1) : pack2(o[19] * f1, o[23] * f1);
        u[6] = pack2(o[1] * f0, o[5] * f0); u[7] = pack2(o[3] * f1, o[7] * f1); u[8] = pack2(o[9] * f0, o[13] * f0); u[9] = pack2(o[11] * f1, o[15] * f1);
      };
      uint8_t* od = hth + (uint32_t)((216 + c * 5) * 2048 + q * 4);
      keep(od);
      uint32_t ua[10], ub[10];
      auto oput = [&](auto IC0) {
        constexpr int i0 = decltype(IC0)::value;
#pragma unroll
        for (int i = i0; i < i0 + 5; i++) stg32(od + ((i % 10) >> 1) * 2048 + (i / 10) * 81920 + (i & 1) * 128, i < 10 ? ua[i] : ub[i - 10]);
      };
      onorm(o0, o1, ua);
      oput(IC<0>());
      if (OPAT) { oput(IC<5>()); nb_arrive<NB_PUB + 5, 288>(); }
      STEP(160, 2, accg, T_O + 1)
      if (!OPAT) { oput(IC<5>()); nb_arrive<NB_PUB + 5, 288>(); }
      if (on) onorm(o2, o3, ub);
      if (OPAT) oput(IC<10>());
      if (OPAT == 2) { oput(IC<15>()); nb_arrive<NB_PUB + 6, 288>(); }
      STEP(160, 2, accg, T_O + 2)
      if (!OPAT) oput(IC<10>());
      if (OPAT == 1) { oput(IC<15>()); nb_arrive<NB_PUB + 6, 288>(); }
      STEP(160, 2, accg, T_O + 3)
      if (!OPAT) { oput(IC<15>()); nb_arrive<NB_PUB + 6, 288>(); }
    }
#pragma unroll 1
    for (int t = T_O + 4; t < 43; t++) { STEPR(160, 2, accg, t) }
    STEP(160, 2, accg, 43, false, 0)

    float accs[40];
    const uint32_t xloc = sb + PH_OFF + tid * 16, xrem = peer + PH_OFF + tid * 16, xg = peer + BAR_OFF + B_XG;
    const uint32_t xa = ((rb * 128 + W * 16 + (lane >> 3)) * D_ + 64 * (a0 + ks) + (lane & 7) * 8) * 2;
    const uint32_t xb = ((rb * 128 + W * 16 + (lane >> 1)) * D_ + 32 * pg + 16 * ks + (lane & 1) * 8) * 2;
#define STEPS(T, ...) mma_step<80, 3, T>(accs, sb, T, DA(3, (T) >> 2), DB(3, (T) >> 2), leader, nw, ##__VA_ARGS__); if (!((T) & 1)) TRC(22 + (T) / 2);
    uint4 xr[5];
    auto ldxr = [&]() {
#pragma unroll
      for (int i = 0; i < 4; i++) xr[i] = ldg128((const char*)p.x + xa + i * 8 * D_);
      xr[4] = ldg128((const char*)p.x + xb);
    };
    if (XRP == 1) ldxr();
    {
      uint32_t u[20];
      mbar_wait(bars + B_XRDY, 0, nw);
      if (GB) { STEPS(44, true) }
      else { wg_wait<0>(); if (leader) mbar_arrive(bars + B_EMPTY + 24); }
      pin(accg);
#pragma unroll
      for (int i = 0; i < 16; i++) u[i] = pack2(accg[32 + 2 * i], accg[33 + 2 * i]);
#pragma unroll
      for (int i = 0; i < 4; i++) u[16 + i] = pack2(ks ? accg[64 + 2 * i] : accg[72 + 2 * i], ks ? accg[65 + 2 * i] : accg[73 + 2 * i]);
      st_async4<0>(xrem, u[0], u[1], u[2], u[3], xg); st_async4<4096>(xrem, u[4], u[5], u[6], u[7], xg);
#pragma unroll
      for (int i = 0; i < 8; i++) accg[32 + i] = ks ? accg[72 + i] : accg[64 + i];
      if (!GB) { mma_step<80, 3, 44, false>(accs, sb, 44, DA(3, 11), DB(3, 11), leader, nw, true); TRC(44); st_async4<8192>(xrem, u[8], u[9], u[10], u[11], xg); }
      STEPS(45)
      if (GB) st_async4<8192>(xrem, u[8], u[9], u[10], u[11], xg);
      st_async4<12288>(xrem, u[12], u[13], u[14], u[15], xg);
      STEPS(46)
      st_async4<16384>(xrem, u[16], u[17], u[18], u[19], xg);
    }
    STEPS(47)
    mbar_wait(bars + B_XS, 0, nw);
    STEPS(48)
    mbar_wait(bars + B_XG, 0, nw);
    uint4 gv[5];
#pragma unroll
    for (int i = 0; i < 5; i++) gv[i] = lds128(xloc + i * 4096);
    if (XRP == 0) ldxr();
    uint32_t gate[20];
    auto gate4 = [&](auto IC0) {
      constexpr int b = decltype(IC0)::value;
      const uint32_t vv[4] = {gv[b].x, gv[b].y, gv[b].z, gv[b].w};
#pragma unroll
      for (int e = 0; e < 4; e++) {
        const uint32_t hv = hmul2bf(vv[e], 0x3f003f00u);
        gate[4 * b + e] = pack2(silu_half(fmaf(accg[8 * b + 2 * e], 0.5f, bf_lo(hv))), silu_half(fmaf(accg[8 * b + 2 * e + 1], 0.5f, bf_hi(hv))));
        asm volatile("" : "+r"(gate[4 * b + e]));
      }
    };
    STEPS(49)
    if (on) gate4(IC<0>());
    STEPS(50)
    if (on) gate4(IC<1>());
    STEPS(51)
    if (on) gate4(IC<2>());
    STEPS(52)
    if (on) gate4(IC<3>());
    STEPS(53)
    if (XRP == 2) ldxr();
    if (on) gate4(IC<4>());
    TRC(49);
    wg_wait<0>();
    pin(accs); TRC(50);
    {
      const uint32_t ost = sb + SLOT + 16384 + W * 2816;
      const uint32_t sta = ost + (lane & 15) * 176 + (lane >> 4) * 16;
#pragma unroll
      for (int b = 0; b < 5; b++)
        asm volatile("stmatrix.sync.aligned.m8n8.x4.shared.b16 [%0], {%1,%2,%3,%4};" ::"r"(sta + b * 32), "r"(hfma2bf(pack2(accs[8 * b], accs[8 * b + 1]), gate[4 * b], 0u)),
                     "r"(hfma2bf(pack2(accs[8 * b + 2], accs[8 * b + 3]), gate[4 * b + 1], 0u)), "r"(hfma2bf(pack2(accs[8 * b + 4], accs[8 * b + 5]), gate[4 * b + 2], 0u)),
                     "r"(hfma2bf(pack2(accs[8 * b + 6], accs[8 * b + 7]), gate[4 * b + 3], 0u)) : "memory");
      __syncwarp();
#pragma unroll
      for (int i = 0; i < 5; i++) {
        const uint4 v = lds128(i < 4 ? ost + (i * 4 + (lane >> 3)) * 176 + (lane & 7) * 16 : ost + (lane >> 1) * 176 + 128 + (lane & 1) * 16);
        stg128(i < 4 ? (char*)p.out + xa + i * 8 * D_ : (char*)p.out + xb, hadd2bf(xr[i].x, v.x), hadd2bf(xr[i].y, v.y), hadd2bf(xr[i].z, v.z), hadd2bf(xr[i].w, v.w));
      }
      TRC(51);
      if (pos == 0 && tid == 0 && nw != ~0u) g_s.flags[FL_EPOCH * 32] = lds32(bars + B_EPOCH) + 1;
    }
  }
}

typedef CUresult (*EncodeFn)(CUtensorMap*, CUtensorMapDataType, cuuint32_t, void*, const cuuint64_t*, const cuuint64_t*, const cuuint32_t*,
                             const cuuint32_t*, CUtensorMapInterleave, CUtensorMapSwizzle, CUtensorMapL2promotion, CUtensorMapFloatOOBfill);

static int make_map(EncodeFn enc, CUtensorMap* m, const void* base, int nd, const cuuint64_t* dims, const cuuint64_t* strides, const cuuint32_t* box,
                    CUtensorMapSwizzle sw = CU_TENSOR_MAP_SWIZZLE_128B) {
  const cuuint32_t es[5] = {1, 1, 1, 1, 1};
  return (int)enc(m, CU_TENSOR_MAP_DATA_TYPE_BFLOAT16, nd, const_cast<void*>(base), dims, strides, box, es, CU_TENSOR_MAP_INTERLEAVE_NONE,
                  sw, CU_TENSOR_MAP_L2_PROMOTION_L2_128B, CU_TENSOR_MAP_FLOAT_OOB_FILL_NONE);
}

extern "C" void kernel_launch(void* const* d_in, const int* in_sizes, int n_in, void* d_out, int out_size) {
  (void)in_sizes; (void)n_in; (void)out_size;
  void* fn = nullptr;
  cudaDriverEntryPointQueryResult qr;
  cudaGetDriverEntryPoint("cuTensorMapEncodeTiled", &fn, cudaEnableDefault, &qr);
  EncodeFn enc = (EncodeFn)fn;
  Params p;
  p.x = (const bf16*)d_in[0]; p.wqkv = (const bf16*)d_in[1]; p.wphi = (const bf16*)d_in[2]; p.wo = (const bf16*)d_in[3];
  p.w1 = (const bf16*)d_in[5]; p.w2 = (const bf16*)d_in[6]; p.out = (bf16*)d_out; p.one = 1;
  for (int i = 0; i < 15; i++) { p.dsw[i] = dhi(1024, 1); p.dns[i] = dhi(128, 0); }
  for (int col = 0; col < 128; col++) {
    const int h = col / 20, d = (col - h * 20 - 4 * (h & 1) + 20) % 20;
    const int f = d < 16 ? (d & 8) + 4 * (d & 1) + ((d & 7) >> 1) : 16 + 2 * (d & 1) + ((d >> 1) & 1);
    p.vrow[col] = (uint16_t)(col < 80 ? 80 + 8 * (f >> 1) + 2 * h + (f & 1) : 160 + col);
  }
  for (int cl = 0; cl < 64; cl++) {
    int grp, t;
    if (cl < 4) { grp = 15; t = cl; }
    else if (cl < 36) { grp = (cl - 4) & 7; t = (cl - 4) >> 3; }
    else { grp = 8 + (cl - 36) % 7; t = (cl - 36) / 7; }
    p.tile[cl] = grp * 8 + t * 2;
  }
  int err = 0;
  void* scr = nullptr;
  cudaGetSymbolAddress(&scr, g_s);
  { const cuuint64_t d[3] = {64, 33, 640}, s[2] = {128, WP_KG}; const cuuint32_t b2[3] = {64, 20, 8}, b3[3] = {64, 13, 8};
    err |= make_map(enc, &p.mWp2, ((Scratch*)scr)->wp, 3, d, s, b2, CU_TENSOR_MAP_SWIZZLE_NONE); err |= make_map(enc, &p.mWp3, ((Scratch*)scr)->wp, 3, d, s, b3, CU_TENSOR_MAP_SWIZZLE_NONE); }
  { const cuuint64_t d[2] = {640, 2048}, s[1] = {1280}; const cuuint32_t b[2] = {64, 128}; err |= make_map(enc, &p.mX, p.x, 2, d, s, b); }
  { const cuuint64_t d[3] = {64, 640, 27}, s[2] = {3456, 128}; const cuuint32_t b[3] = {64, 64, 3}; err |= make_map(enc, &p.mW1, p.w1, 3, d, s, b);
    const cuuint32_t bs[3] = {64, 40, 3}; err |= make_map(enc, &p.mW1s, p.w1, 3, d, s, bs); }
  { const cuuint64_t d[2] = {1728, 640}, s[1] = {3456}; const cuuint32_t b[2] = {24, 40}; err |= make_map(enc, &p.mWts, p.w1, 2, d, s, b, CU_TENSOR_MAP_SWIZZLE_NONE); }
  { const cuuint64_t d[3] = {640, 640, 3}, s[2] = {3840, 1280}; const cuuint32_t b[3] = {80, 40, 3}; err |= make_map(enc, &p.mQs, p.wqkv, 3, d, s, b, CU_TENSOR_MAP_SWIZZLE_NONE); }
  { const cuuint64_t d[5] = {64, 8, 216, 1, 10}, s[4] = {1280, 10240, 1280, 128}; const cuuint32_t b[5] = {64, 8, 8, 1, 1}; err |= make_map(enc, &p.mW2n, p.w2, 5, d, s, b);
    const cuuint32_t bh[5] = {64, 8, 4, 1, 1}; err |= make_map(enc, &p.mW2h, p.w2, 5, d, s, bh); }
  { const cuuint64_t d[5] = {64, 2, 216, 4, 10}, s[4] = {1280, 10240, 2560, 128}; const cuuint32_t b[5] = {64, 2, 8, 4, 1}; err |= make_map(enc, &p.mW2a, p.w2, 5, d, s, b); }
  if (err) return;
  cudaFuncSetAttribute(fused_kernel, cudaFuncAttributeMaxDynamicSharedMemorySize, SMEM_BYTES);
  fused_kernel<<<128, NTHR, SMEM_BYTES>>>(p);
}
```
